```python
import torch

def _softmax(x, axis=-1):
    return torch.softmax(x, dim=axis)
def _gelu(x):
    return torch.nn.functional.gelu(x, approximate="tanh")
def _silu(x):
    return torch.nn.functional.silu(x)
def _sigmoid(x):
    return torch.sigmoid(x)
def _layernorm(x, axis=-1, eps=1e-5):
    m = x.mean(dim=axis, keepdim=True)
    v = x.var(dim=axis, keepdim=True, unbiased=False)
    return (x - m) / torch.sqrt(v + eps)
def _scatter_add(tgt, idx, src, axis=0):
    return tgt.clone().index_add_(axis, idx, src)
def _segment_sum(src, seg, n):
    out = torch.zeros((n,) + src.shape[1:], dtype=src.dtype)
    return out.index_add_(0, seg, src)
def _pad(x, pw):
    flat = tuple(v for pair in reversed(pw) for v in pair)
    return torch.nn.functional.pad(x, flat)

kernel_name = 'standalone__deep_cross_pnn__recsys'

def setup_inputs():

    _w = (lambda a: (lambda t: t.to(torch.bfloat16) if t.is_floating_point() else t)(torch.as_tensor(a)))
    B, F, D, V = 16384, 100, 64, min(100000, 100000)
    H = 4 * D
    return {
        "idx": _w((lambda lo, hi, *s: torch.randint(lo, hi, s))(0, V, B, F).to(torch.int64)),
        "table": _w((lambda *s: torch.randn(*s, dtype=torch.bfloat16) * 1.6)(V, D) * (D ** -0.5)),
        "w_p": _w((lambda *s: torch.randn(*s, dtype=torch.bfloat16) * 0.05)(F * F) * ((F * F) ** -0.5)),
        "w1": _w((lambda *s: torch.randn(*s, dtype=torch.bfloat16) * 1.6)(F * D, H) * ((F * D) ** -0.5)),
        "b1": _w((lambda *s: torch.randn(*s, dtype=torch.bfloat16) * 12.8)(H) * 0.01),
        "w2": _w((lambda *s: torch.randn(*s, dtype=torch.bfloat16) * 0.05)(H) * (H ** -0.5)),
        "b2": _w((lambda *s: torch.randn(*s, dtype=torch.bfloat16) * 1.6)(1) * 0.01),
    }

def reference(idx, table, w_p, w1, b1, w2, b2):
    emb = table[idx]
    B = emb.shape[0]; F = emb.shape[1]; D = emb.shape[2]
    ip = torch.einsum('bid,bjd->bij', emb, emb)
    ip = ip.reshape(B, F * F)
    logit_p = ip @ w_p
    z = emb.reshape(B, F * D)
    h = _gelu(z @ w1 + b1)
    logit_d = h @ w2 + b2
    return logit_p + logit_d
```

```cpp
#include <cuda_runtime.h>
#include <cuda_bf16.h>
#include <cuda.h>
#include <stdint.h>

namespace {

constexpr int NF = 100;
constexpr int ND = 64;
constexpr int NH = 256;
constexpr int TILE_M = 128;
constexpr int NS = 3;
constexpr int NP = 4;

#define TAILV 2
#define EBS 16
#define EPI 1
#define TILING 5
#define JSPLIT 6
constexpr int JS = JSPLIT;
__host__ __device__ constexpr int s_j0(int P) { return P ? JS : 0; }
__host__ __device__ constexpr int s_j1(int P) { return P ? 13 : JS; }
__host__ __device__ constexpr int s_nb(int P, int kk) {
    return s_j1(P) - (2 * kk > s_j0(P) ? 2 * kk : s_j0(P)) > 0 ? s_j1(P) - (2 * kk > s_j0(P) ? 2 * kk : s_j0(P)) : 0;
}
__host__ __device__ constexpr int s_base(int P, int kk) {
    return kk > 0 ? s_base(P, kk - 1) + s_nb(P, kk - 1) : P > 0 ? s_base(P - 1, 7) : 0;
}
constexpr int NG = 2, NGA = 1;
constexpr int U_TILES = s_base(2, 0);
constexpr int NBA = JS, KSA = (JS + 1) / 2;
constexpr int NACC_A = 4 * NBA, NACC_B = 4 * (13 - NBA);

constexpr uint32_t STAGE_BYTES = 49152;
constexpr uint32_t W_OFF      = 16384;
constexpr uint32_t OFF_U      = NS * STAGE_BYTES;
constexpr uint32_t U_BYTES    = U_TILES * 256;
constexpr uint32_t OFF_P      = OFF_U + ((U_BYTES + 1023) & ~1023u);
constexpr uint32_t P_BYTES    = NF * 128;
constexpr uint32_t OFF_BW     = OFF_P + NP * P_BYTES + 512;
constexpr uint32_t OFF_PN     = OFF_BW + 1024;
#define HS_SLOTS 8
constexpr int HS = HS_SLOTS;
constexpr uint32_t OFF_HU     = 2 * HS * P_BYTES;
constexpr uint32_t OFF_HPN    = OFF_HU + U_BYTES;
constexpr uint32_t OFF_HW     = (OFF_HU - NF * NF * 2) & ~127u;
constexpr uint32_t H_END      = OFF_HPN + 2 * 192 * 16;
constexpr uint32_t OFF_W2F    = OFF_PN + TILE_M * 4 * 4;
constexpr uint32_t M_END      = OFF_W2F + 1024;
constexpr uint32_t OFF_BAR    = M_END > H_END ? M_END : H_END;
constexpr uint32_t SMEM_USED  = OFF_BAR + 512;
constexpr uint32_t SMEM_BYTES = SMEM_USED + 1024;
static_assert(SMEM_BYTES <= 232448, "smem");
static_assert(NF * NF * 2 <= NP * P_BYTES, "w_p staging");

constexpr uint32_t BAR_FULL_M  = 0;
constexpr uint32_t BAR_EMPTY_M = 8 * NS;
constexpr uint32_t BAR_FULL_P  = 16 * NS;
constexpr uint32_t BAR_EMPTY_P = 16 * NS + 8 * NP;
constexpr uint32_t BAR_WP      = 16 * NS + 16 * NP;
constexpr uint32_t BAR_U       = BAR_WP + 8;
constexpr uint32_t BAR_GO      = 448;

template <int OFFA, int OFFB, int HI>
__device__ __forceinline__ void wgmma_ss_n256(float* d, uint32_t alo, uint32_t blo) {
  asm volatile("{\n.reg .b32 lo;\n.reg .b64 da, db;\n"
    "add.u32 lo, %128, %130;\nmov.b64 da, {lo, %132};\n"
    "add.u32 lo, %129, %131;\nmov.b64 db, {lo, %132};\n"
    "wgmma.mma_async.sync.aligned.m64n256k16.f32.bf16.bf16 "
    "{%0,%1,%2,%3,%4,%5,%6,%7,%8,%9,%10,%11,%12,%13,%14,%15,%16,%17,%18,%19,%20,%21,%22,%23,%24,%25,%26,%27,%28,%29,%30,%31,%32,%33,%34,%35,%36,%37,%38,%39,%40,%41,%42,%43,%44,%45,%46,%47,%48,%49,%50,%51,%52,%53,%54,%55,%56,%57,%58,%59,%60,%61,%62,%63,%64,%65,%66,%67,%68,%69,%70,%71,%72,%73,%74,%75,%76,%77,%78,%79,%80,%81,%82,%83,%84,%85,%86,%87,%88,%89,%90,%91,%92,%93,%94,%95,%96,%97,%98,%99,%100,%101,%102,%103,%104,%105,%106,%107,%108,%109,%110,%111,%112,%113,%114,%115,%116,%117,%118,%119,%120,%121,%122,%123,%124,%125,%126,%127}, da, db, 1, 1, 1, 0, 1;\n}\n"
    : "+f"(d[0]), "+f"(d[1]), "+f"(d[2]), "+f"(d[3]), "+f"(d[4]), "+f"(d[5]), "+f"(d[6]), "+f"(d[7]),
      "+f"(d[8]), "+f"(d[9]), "+f"(d[10]), "+f"(d[11]), "+f"(d[12]), "+f"(d[13]), "+f"(d[14]), "+f"(d[15]),
      "+f"(d[16]), "+f"(d[17]), "+f"(d[18]), "+f"(d[19]), "+f"(d[20]), "+f"(d[21]), "+f"(d[22]), "+f"(d[23]),
      "+f"(d[24]), "+f"(d[25]), "+f"(d[26]), "+f"(d[27]), "+f"(d[28]), "+f"(d[29]), "+f"(d[30]), "+f"(d[31]),
      "+f"(d[32]), "+f"(d[33]), "+f"(d[34]), "+f"(d[35]), "+f"(d[36]), "+f"(d[37]), "+f"(d[38]), "+f"(d[39]),
      "+f"(d[40]), "+f"(d[41]), "+f"(d[42]), "+f"(d[43]), "+f"(d[44]), "+f"(d[45]), "+f"(d[46]), "+f"(d[47]),
      "+f"(d[48]), "+f"(d[49]), "+f"(d[50]), "+f"(d[51]), "+f"(d[52]), "+f"(d[53]), "+f"(d[54]), "+f"(d[55]),
      "+f"(d[56]), "+f"(d[57]), "+f"(d[58]), "+f"(d[59]), "+f"(d[60]), "+f"(d[61]), "+f"(d[62]), "+f"(d[63]),
      "+f"(d[64]), "+f"(d[65]), "+f"(d[66]), "+f"(d[67]), "+f"(d[68]), "+f"(d[69]), "+f"(d[70]), "+f"(d[71]),
      "+f"(d[72]), "+f"(d[73]), "+f"(d[74]), "+f"(d[75]), "+f"(d[76]), "+f"(d[77]), "+f"(d[78]), "+f"(d[79]),
      "+f"(d[80]), "+f"(d[81]), "+f"(d[82]), "+f"(d[83]), "+f"(d[84]), "+f"(d[85]), "+f"(d[86]), "+f"(d[87]),
      "+f"(d[88]), "+f"(d[89]), "+f"(d[90]), "+f"(d[91]), "+f"(d[92]), "+f"(d[93]), "+f"(d[94]), "+f"(d[95]),
      "+f"(d[96]), "+f"(d[97]), "+f"(d[98]), "+f"(d[99]), "+f"(d[100]), "+f"(d[101]), "+f"(d[102]), "+f"(d[103]),
      "+f"(d[104]), "+f"(d[105]), "+f"(d[106]), "+f"(d[107]), "+f"(d[108]), "+f"(d[109]), "+f"(d[110]), "+f"(d[111]),
      "+f"(d[112]), "+f"(d[113]), "+f"(d[114]), "+f"(d[115]), "+f"(d[116]), "+f"(d[117]), "+f"(d[118]), "+f"(d[119]),
      "+f"(d[120]), "+f"(d[121]), "+f"(d[122]), "+f"(d[123]), "+f"(d[124]), "+f"(d[125]), "+f"(d[126]), "+f"(d[127])
    : "r"(alo), "r"(blo), "n"(OFFA), "n"(OFFB), "n"(HI));
}
template <int OFF, int HI>
__device__ __forceinline__ void wgmma_rs_n104_init(float* d, uint32_t a0, uint32_t a1, uint32_t a2, uint32_t a3, uint32_t blo) {
  asm volatile("{\n.reg .pred p;\n.reg .b32 lo;\n.reg .b64 db;\n"
    "setp.ne.b32 p, 0, 0;\nadd.u32 lo, %56, %57;\nmov.b64 db, {lo, %58};\n"
    "wgmma.mma_async.sync.aligned.m64n104k16.f32.bf16.bf16 "
    "{%0,%1,%2,%3,%4,%5,%6,%7,%8,%9,%10,%11,%12,%13,%14,%15,%16,%17,%18,%19,%20,%21,%22,%23,%24,%25,%26,%27,%28,%29,%30,%31,%32,%33,%34,%35,%36,%37,%38,%39,%40,%41,%42,%43,%44,%45,%46,%47,%48,%49,%50,%51}, {%52,%53,%54,%55}, db, p, 1, 1, 0;\n}\n"
    : "=f"(d[0]), "=f"(d[1]), "=f"(d[2]), "=f"(d[3]), "=f"(d[4]), "=f"(d[5]), "=f"(d[6]), "=f"(d[7]),
      "=f"(d[8]), "=f"(d[9]), "=f"(d[10]), "=f"(d[11]), "=f"(d[12]), "=f"(d[13]), "=f"(d[14]), "=f"(d[15]),
      "=f"(d[16]), "=f"(d[17]), "=f"(d[18]), "=f"(d[19]), "=f"(d[20]), "=f"(d[21]), "=f"(d[22]), "=f"(d[23]),
      "=f"(d[24]), "=f"(d[25]), "=f"(d[26]), "=f"(d[27]), "=f"(d[28]), "=f"(d[29]), "=f"(d[30]), "=f"(d[31]),
      "=f"(d[32]), "=f"(d[33]), "=f"(d[34]), "=f"(d[35]), "=f"(d[36]), "=f"(d[37]), "=f"(d[38]), "=f"(d[39]),
      "=f"(d[40]), "=f"(d[41]), "=f"(d[42]), "=f"(d[43]), "=f"(d[44]), "=f"(d[45]), "=f"(d[46]), "=f"(d[47]),
      "=f"(d[48]), "=f"(d[49]), "=f"(d[50]), "=f"(d[51])
    : "r"(a0), "r"(a1), "r"(a2), "r"(a3), "r"(blo), "n"(OFF), "n"(HI));
}
template <int OFF, int HI>
__device__ __forceinline__ void wgmma_rs_n104_acc(float* d, uint32_t a0, uint32_t a1, uint32_t a2, uint32_t a3, uint32_t blo) {
  asm volatile("{\n.reg .pred p;\n.reg .b32 lo;\n.reg .b64 db;\n"
    "setp.ne.b32 p, 1, 0;\nadd.u32 lo, %56, %57;\nmov.b64 db, {lo, %58};\n"
    "wgmma.mma_async.sync.aligned.m64n104k16.f32.bf16.bf16 "
    "{%0,%1,%2,%3,%4,%5,%6,%7,%8,%9,%10,%11,%12,%13,%14,%15,%16,%17,%18,%19,%20,%21,%22,%23,%24,%25,%26,%27,%28,%29,%30,%31,%32,%33,%34,%35,%36,%37,%38,%39,%40,%41,%42,%43,%44,%45,%46,%47,%48,%49,%50,%51}, {%52,%53,%54,%55}, db, p, 1, 1, 0;\n}\n"
    : "+f"(d[0]), "+f"(d[1]), "+f"(d[2]), "+f"(d[3]), "+f"(d[4]), "+f"(d[5]), "+f"(d[6]), "+f"(d[7]),
      "+f"(d[8]), "+f"(d[9]), "+f"(d[10]), "+f"(d[11]), "+f"(d[12]), "+f"(d[13]), "+f"(d[14]), "+f"(d[15]),
      "+f"(d[16]), "+f"(d[17]), "+f"(d[18]), "+f"(d[19]), "+f"(d[20]), "+f"(d[21]), "+f"(d[22]), "+f"(d[23]),
      "+f"(d[24]), "+f"(d[25]), "+f"(d[26]), "+f"(d[27]), "+f"(d[28]), "+f"(d[29]), "+f"(d[30]), "+f"(d[31]),
      "+f"(d[32]), "+f"(d[33]), "+f"(d[34]), "+f"(d[35]), "+f"(d[36]), "+f"(d[37]), "+f"(d[38]), "+f"(d[39]),
      "+f"(d[40]), "+f"(d[41]), "+f"(d[42]), "+f"(d[43]), "+f"(d[44]), "+f"(d[45]), "+f"(d[46]), "+f"(d[47]),
      "+f"(d[48]), "+f"(d[49]), "+f"(d[50]), "+f"(d[51])
    : "r"(a0), "r"(a1), "r"(a2), "r"(a3), "r"(blo), "n"(OFF), "n"(HI));
}
template <int OFF, int HI>
__device__ __forceinline__ void wgmma_rs_n88_init(float* d, uint32_t a0, uint32_t a1, uint32_t a2, uint32_t a3, uint32_t blo) {
  asm volatile("{\n.reg .pred p;\n.reg .b32 lo;\n.reg .b64 db;\n"
    "setp.ne.b32 p, 0, 0;\nadd.u32 lo, %48, %49;\nmov.b64 db, {lo, %50};\n"
    "wgmma.mma_async.sync.aligned.m64n88k16.f32.bf16.bf16 "
    "{%0,%1,%2,%3,%4,%5,%6,%7,%8,%9,%10,%11,%12,%13,%14,%15,%16,%17,%18,%19,%20,%21,%22,%23,%24,%25,%26,%27,%28,%29,%30,%31,%32,%33,%34,%35,%36,%37,%38,%39,%40,%41,%42,%43}, {%44,%45,%46,%47}, db, p, 1, 1, 0;\n}\n"
    : "=f"(d[0]), "=f"(d[1]), "=f"(d[2]), "=f"(d[3]), "=f"(d[4]), "=f"(d[5]), "=f"(d[6]), "=f"(d[7]),
      "=f"(d[8]), "=f"(d[9]), "=f"(d[10]), "=f"(d[11]), "=f"(d[12]), "=f"(d[13]), "=f"(d[14]), "=f"(d[15]),
      "=f"(d[16]), "=f"(d[17]), "=f"(d[18]), "=f"(d[19]), "=f"(d[20]), "=f"(d[21]), "=f"(d[22]), "=f"(d[23]),
      "=f"(d[24]), "=f"(d[25]), "=f"(d[26]), "=f"(d[27]), "=f"(d[28]), "=f"(d[29]), "=f"(d[30]), "=f"(d[31]),
      "=f"(d[32]), "=f"(d[33]), "=f"(d[34]), "=f"(d[35]), "=f"(d[36]), "=f"(d[37]), "=f"(d[38]), "=f"(d[39]),
      "=f"(d[40]), "=f"(d[41]), "=f"(d[42]), "=f"(d[43])
    : "r"(a0), "r"(a1), "r"(a2), "r"(a3), "r"(blo), "n"(OFF), "n"(HI));
}
template <int OFF, int HI>
__device__ __forceinline__ void wgmma_rs_n88_acc(float* d, uint32_t a0, uint32_t a1, uint32_t a2, uint32_t a3, uint32_t blo) {
  asm volatile("{\n.reg .pred p;\n.reg .b32 lo;\n.reg .b64 db;\n"
    "setp.ne.b32 p, 1, 0;\nadd.u32 lo, %48, %49;\nmov.b64 db, {lo, %50};\n"
    "wgmma.mma_async.sync.aligned.m64n88k16.f32.bf16.bf16 "
    "{%0,%1,%2,%3,%4,%5,%6,%7,%8,%9,%10,%11,%12,%13,%14,%15,%16,%17,%18,%19,%20,%21,%22,%23,%24,%25,%26,%27,%28,%29,%30,%31,%32,%33,%34,%35,%36,%37,%38,%39,%40,%41,%42,%43}, {%44,%45,%46,%47}, db, p, 1, 1, 0;\n}\n"
    : "+f"(d[0]), "+f"(d[1]), "+f"(d[2]), "+f"(d[3]), "+f"(d[4]), "+f"(d[5]), "+f"(d[6]), "+f"(d[7]),
      "+f"(d[8]), "+f"(d[9]), "+f"(d[10]), "+f"(d[11]), "+f"(d[12]), "+f"(d[13]), "+f"(d[14]), "+f"(d[15]),
      "+f"(d[16]), "+f"(d[17]), "+f"(d[18]), "+f"(d[19]), "+f"(d[20]), "+f"(d[21]), "+f"(d[22]), "+f"(d[23]),
      "+f"(d[24]), "+f"(d[25]), "+f"(d[26]), "+f"(d[27]), "+f"(d[28]), "+f"(d[29]), "+f"(d[30]), "+f"(d[31]),
      "+f"(d[32]), "+f"(d[33]), "+f"(d[34]), "+f"(d[35]), "+f"(d[36]), "+f"(d[37]), "+f"(d[38]), "+f"(d[39]),
      "+f"(d[40]), "+f"(d[41]), "+f"(d[42]), "+f"(d[43])
    : "r"(a0), "r"(a1), "r"(a2), "r"(a3), "r"(blo), "n"(OFF), "n"(HI));
}
template <int OFF, int HI>
__device__ __forceinline__ void wgmma_rs_n72_init(float* d, uint32_t a0, uint32_t a1, uint32_t a2, uint32_t a3, uint32_t blo) {
  asm volatile("{\n.reg .pred p;\n.reg .b32 lo;\n.reg .b64 db;\n"
    "setp.ne.b32 p, 0, 0;\nadd.u32 lo, %40, %41;\nmov.b64 db, {lo, %42};\n"
    "wgmma.mma_async.sync.aligned.m64n72k16.f32.bf16.bf16 "
    "{%0,%1,%2,%3,%4,%5,%6,%7,%8,%9,%10,%11,%12,%13,%14,%15,%16,%17,%18,%19,%20,%21,%22,%23,%24,%25,%26,%27,%28,%29,%30,%31,%32,%33,%34,%35}, {%36,%37,%38,%39}, db, p, 1, 1, 0;\n}\n"
    : "=f"(d[0]), "=f"(d[1]), "=f"(d[2]), "=f"(d[3]), "=f"(d[4]), "=f"(d[5]), "=f"(d[6]), "=f"(d[7]),
      "=f"(d[8]), "=f"(d[9]), "=f"(d[10]), "=f"(d[11]), "=f"(d[12]), "=f"(d[13]), "=f"(d[14]), "=f"(d[15]),
      "=f"(d[16]), "=f"(d[17]), "=f"(d[18]), "=f"(d[19]), "=f"(d[20]), "=f"(d[21]), "=f"(d[22]), "=f"(d[23]),
      "=f"(d[24]), "=f"(d[25]), "=f"(d[26]), "=f"(d[27]), "=f"(d[28]), "=f"(d[29]), "=f"(d[30]), "=f"(d[31]),
      "=f"(d[32]), "=f"(d[33]), "=f"(d[34]), "=f"(d[35])
    : "r"(a0), "r"(a1), "r"(a2), "r"(a3), "r"(blo), "n"(OFF), "n"(HI));
}
template <int OFF, int HI>
__device__ __forceinline__ void wgmma_rs_n72_acc(float* d, uint32_t a0, uint32_t a1, uint32_t a2, uint32_t a3, uint32_t blo) {
  asm volatile("{\n.reg .pred p;\n.reg .b32 lo;\n.reg .b64 db;\n"
    "setp.ne.b32 p, 1, 0;\nadd.u32 lo, %40, %41;\nmov.b64 db, {lo, %42};\n"
    "wgmma.mma_async.sync.aligned.m64n72k16.f32.bf16.bf16 "
    "{%0,%1,%2,%3,%4,%5,%6,%7,%8,%9,%10,%11,%12,%13,%14,%15,%16,%17,%18,%19,%20,%21,%22,%23,%24,%25,%26,%27,%28,%29,%30,%31,%32,%33,%34,%35}, {%36,%37,%38,%39}, db, p, 1, 1, 0;\n}\n"
    : "+f"(d[0]), "+f"(d[1]), "+f"(d[2]), "+f"(d[3]), "+f"(d[4]), "+f"(d[5]), "+f"(d[6]), "+f"(d[7]),
      "+f"(d[8]), "+f"(d[9]), "+f"(d[10]), "+f"(d[11]), "+f"(d[12]), "+f"(d[13]), "+f"(d[14]), "+f"(d[15]),
      "+f"(d[16]), "+f"(d[17]), "+f"(d[18]), "+f"(d[19]), "+f"(d[20]), "+f"(d[21]), "+f"(d[22]), "+f"(d[23]),
      "+f"(d[24]), "+f"(d[25]), "+f"(d[26]), "+f"(d[27]), "+f"(d[28]), "+f"(d[29]), "+f"(d[30]), "+f"(d[31]),
      "+f"(d[32]), "+f"(d[33]), "+f"(d[34]), "+f"(d[35])
    : "r"(a0), "r"(a1), "r"(a2), "r"(a3), "r"(blo), "n"(OFF), "n"(HI));
}
template <int OFF, int HI>
__device__ __forceinline__ void wgmma_rs_n64_init(float* d, uint32_t a0, uint32_t a1, uint32_t a2, uint32_t a3, uint32_t blo) {
  asm volatile("{\n.reg .pred p;\n.reg .b32 lo;\n.reg .b64 db;\n"
    "setp.ne.b32 p, 0, 0;\nadd.u32 lo, %36, %37;\nmov.b64 db, {lo, %38};\n"
    "wgmma.mma_async.sync.aligned.m64n64k16.f32.bf16.bf16 "
    "{%0,%1,%2,%3,%4,%5,%6,%7,%8,%9,%10,%11,%12,%13,%14,%15,%16,%17,%18,%19,%20,%21,%22,%23,%24,%25,%26,%27,%28,%29,%30,%31}, {%32,%33,%34,%35}, db, p, 1, 1, 0;\n}\n"
    : "=f"(d[0]), "=f"(d[1]), "=f"(d[2]), "=f"(d[3]), "=f"(d[4]), "=f"(d[5]), "=f"(d[6]), "=f"(d[7]),
      "=f"(d[8]), "=f"(d[9]), "=f"(d[10]), "=f"(d[11]), "=f"(d[12]), "=f"(d[13]), "=f"(d[14]), "=f"(d[15]),
      "=f"(d[16]), "=f"(d[17]), "=f"(d[18]), "=f"(d[19]), "=f"(d[20]), "=f"(d[21]), "=f"(d[22]), "=f"(d[23]),
      "=f"(d[24]), "=f"(d[25]), "=f"(d[26]), "=f"(d[27]), "=f"(d[28]), "=f"(d[29]), "=f"(d[30]), "=f"(d[31])
    : "r"(a0), "r"(a1), "r"(a2), "r"(a3), "r"(blo), "n"(OFF), "n"(HI));
}
template <int OFF, int HI>
__device__ __forceinline__ void wgmma_rs_n64_acc(float* d, uint32_t a0, uint32_t a1, uint32_t a2, uint32_t a3, uint32_t blo) {
  asm volatile("{\n.reg .pred p;\n.reg .b32 lo;\n.reg .b64 db;\n"
    "setp.ne.b32 p, 1, 0;\nadd.u32 lo, %36, %37;\nmov.b64 db, {lo, %38};\n"
    "wgmma.mma_async.sync.aligned.m64n64k16.f32.bf16.bf16 "
    "{%0,%1,%2,%3,%4,%5,%6,%7,%8,%9,%10,%11,%12,%13,%14,%15,%16,%17,%18,%19,%20,%21,%22,%23,%24,%25,%26,%27,%28,%29,%30,%31}, {%32,%33,%34,%35}, db, p, 1, 1, 0;\n}\n"
    : "+f"(d[0]), "+f"(d[1]), "+f"(d[2]), "+f"(d[3]), "+f"(d[4]), "+f"(d[5]), "+f"(d[6]), "+f"(d[7]),
      "+f"(d[8]), "+f"(d[9]), "+f"(d[10]), "+f"(d[11]), "+f"(d[12]), "+f"(d[13]), "+f"(d[14]), "+f"(d[15]),
      "+f"(d[16]), "+f"(d[17]), "+f"(d[18]), "+f"(d[19]), "+f"(d[20]), "+f"(d[21]), "+f"(d[22]), "+f"(d[23]),
      "+f"(d[24]), "+f"(d[25]), "+f"(d[26]), "+f"(d[27]), "+f"(d[28]), "+f"(d[29]), "+f"(d[30]), "+f"(d[31])
    : "r"(a0), "r"(a1), "r"(a2), "r"(a3), "r"(blo), "n"(OFF), "n"(HI));
}
template <int OFF, int HI>
__device__ __forceinline__ void wgmma_rs_n56_init(float* d, uint32_t a0, uint32_t a1, uint32_t a2, uint32_t a3, uint32_t blo) {
  asm volatile("{\n.reg .pred p;\n.reg .b32 lo;\n.reg .b64 db;\n"
    "setp.ne.b32 p, 0, 0;\nadd.u32 lo, %32, %33;\nmov.b64 db, {lo, %34};\n"
    "wgmma.mma_async.sync.aligned.m64n56k16.f32.bf16.bf16 "
    "{%0,%1,%2,%3,%4,%5,%6,%7,%8,%9,%10,%11,%12,%13,%14,%15,%16,%17,%18,%19,%20,%21,%22,%23,%24,%25,%26,%27}, {%28,%29,%30,%31}, db, p, 1, 1, 0;\n}\n"
    : "=f"(d[0]), "=f"(d[1]), "=f"(d[2]), "=f"(d[3]), "=f"(d[4]), "=f"(d[5]), "=f"(d[6]), "=f"(d[7]),
      "=f"(d[8]), "=f"(d[9]), "=f"(d[10]), "=f"(d[11]), "=f"(d[12]), "=f"(d[13]), "=f"(d[14]), "=f"(d[15]),
      "=f"(d[16]), "=f"(d[17]), "=f"(d[18]), "=f"(d[19]), "=f"(d[20]), "=f"(d[21]), "=f"(d[22]), "=f"(d[23]),
      "=f"(d[24]), "=f"(d[25]), "=f"(d[26]), "=f"(d[27])
    : "r"(a0), "r"(a1), "r"(a2), "r"(a3), "r"(blo), "n"(OFF), "n"(HI));
}
template <int OFF, int HI>
__device__ __forceinline__ void wgmma_rs_n56_acc(float* d, uint32_t a0, uint32_t a1, uint32_t a2, uint32_t a3, uint32_t blo) {
  asm volatile("{\n.reg .pred p;\n.reg .b32 lo;\n.reg .b64 db;\n"
    "setp.ne.b32 p, 1, 0;\nadd.u32 lo, %32, %33;\nmov.b64 db, {lo, %34};\n"
    "wgmma.mma_async.sync.aligned.m64n56k16.f32.bf16.bf16 "
    "{%0,%1,%2,%3,%4,%5,%6,%7,%8,%9,%10,%11,%12,%13,%14,%15,%16,%17,%18,%19,%20,%21,%22,%23,%24,%25,%26,%27}, {%28,%29,%30,%31}, db, p, 1, 1, 0;\n}\n"
    : "+f"(d[0]), "+f"(d[1]), "+f"(d[2]), "+f"(d[3]), "+f"(d[4]), "+f"(d[5]), "+f"(d[6]), "+f"(d[7]),
      "+f"(d[8]), "+f"(d[9]), "+f"(d[10]), "+f"(d[11]), "+f"(d[12]), "+f"(d[13]), "+f"(d[14]), "+f"(d[15]),
      "+f"(d[16]), "+f"(d[17]), "+f"(d[18]), "+f"(d[19]), "+f"(d[20]), "+f"(d[21]), "+f"(d[22]), "+f"(d[23]),
      "+f"(d[24]), "+f"(d[25]), "+f"(d[26]), "+f"(d[27])
    : "r"(a0), "r"(a1), "r"(a2), "r"(a3), "r"(blo), "n"(OFF), "n"(HI));
}
template <int OFF, int HI>
__device__ __forceinline__ void wgmma_rs_n48_init(float* d, uint32_t a0, uint32_t a1, uint32_t a2, uint32_t a3, uint32_t blo) {
  asm volatile("{\n.reg .pred p;\n.reg .b32 lo;\n.reg .b64 db;\n"
    "setp.ne.b32 p, 0, 0;\nadd.u32 lo, %28, %29;\nmov.b64 db, {lo, %30};\n"
    "wgmma.mma_async.sync.aligned.m64n48k16.f32.bf16.bf16 "
    "{%0,%1,%2,%3,%4,%5,%6,%7,%8,%9,%10,%11,%12,%13,%14,%15,%16,%17,%18,%19,%20,%21,%22,%23}, {%24,%25,%26,%27}, db, p, 1, 1, 0;\n}\n"
    : "=f"(d[0]), "=f"(d[1]), "=f"(d[2]), "=f"(d[3]), "=f"(d[4]), "=f"(d[5]), "=f"(d[6]), "=f"(d[7]),
      "=f"(d[8]), "=f"(d[9]), "=f"(d[10]), "=f"(d[11]), "=f"(d[12]), "=f"(d[13]), "=f"(d[14]), "=f"(d[15]),
      "=f"(d[16]), "=f"(d[17]), "=f"(d[18]), "=f"(d[19]), "=f"(d[20]), "=f"(d[21]), "=f"(d[22]), "=f"(d[23])
    : "r"(a0), "r"(a1), "r"(a2), "r"(a3), "r"(blo), "n"(OFF), "n"(HI));
}
template <int OFF, int HI>
__device__ __forceinline__ void wgmma_rs_n48_acc(float* d, uint32_t a0, uint32_t a1, uint32_t a2, uint32_t a3, uint32_t blo) {
  asm volatile("{\n.reg .pred p;\n.reg .b32 lo;\n.reg .b64 db;\n"
    "setp.ne.b32 p, 1, 0;\nadd.u32 lo, %28, %29;\nmov.b64 db, {lo, %30};\n"
    "wgmma.mma_async.sync.aligned.m64n48k16.f32.bf16.bf16 "
    "{%0,%1,%2,%3,%4,%5,%6,%7,%8,%9,%10,%11,%12,%13,%14,%15,%16,%17,%18,%19,%20,%21,%22,%23}, {%24,%25,%26,%27}, db, p, 1, 1, 0;\n}\n"
    : "+f"(d[0]), "+f"(d[1]), "+f"(d[2]), "+f"(d[3]), "+f"(d[4]), "+f"(d[5]), "+f"(d[6]), "+f"(d[7]),
      "+f"(d[8]), "+f"(d[9]), "+f"(d[10]), "+f"(d[11]), "+f"(d[12]), "+f"(d[13]), "+f"(d[14]), "+f"(d[15]),
      "+f"(d[16]), "+f"(d[17]), "+f"(d[18]), "+f"(d[19]), "+f"(d[20]), "+f"(d[21]), "+f"(d[22]), "+f"(d[23])
    : "r"(a0), "r"(a1), "r"(a2), "r"(a3), "r"(blo), "n"(OFF), "n"(HI));
}
template <int OFF, int HI>
__device__ __forceinline__ void wgmma_rs_n40_init(float* d, uint32_t a0, uint32_t a1, uint32_t a2, uint32_t a3, uint32_t blo) {
  asm volatile("{\n.reg .pred p;\n.reg .b32 lo;\n.reg .b64 db;\n"
    "setp.ne.b32 p, 0, 0;\nadd.u32 lo, %24, %25;\nmov.b64 db, {lo, %26};\n"
    "wgmma.mma_async.sync.aligned.m64n40k16.f32.bf16.bf16 "
    "{%0,%1,%2,%3,%4,%5,%6,%7,%8,%9,%10,%11,%12,%13,%14,%15,%16,%17,%18,%19}, {%20,%21,%22,%23}, db, p, 1, 1, 0;\n}\n"
    : "=f"(d[0]), "=f"(d[1]), "=f"(d[2]), "=f"(d[3]), "=f"(d[4]), "=f"(d[5]), "=f"(d[6]), "=f"(d[7]),
      "=f"(d[8]), "=f"(d[9]), "=f"(d[10]), "=f"(d[11]), "=f"(d[12]), "=f"(d[13]), "=f"(d[14]), "=f"(d[15]),
      "=f"(d[16]), "=f"(d[17]), "=f"(d[18]), "=f"(d[19])
    : "r"(a0), "r"(a1), "r"(a2), "r"(a3), "r"(blo), "n"(OFF), "n"(HI));
}
template <int OFF, int HI>
__device__ __forceinline__ void wgmma_rs_n40_acc(float* d, uint32_t a0, uint32_t a1, uint32_t a2, uint32_t a3, uint32_t blo) {
  asm volatile("{\n.reg .pred p;\n.reg .b32 lo;\n.reg .b64 db;\n"
    "setp.ne.b32 p, 1, 0;\nadd.u32 lo, %24, %25;\nmov.b64 db, {lo, %26};\n"
    "wgmma.mma_async.sync.aligned.m64n40k16.f32.bf16.bf16 "
    "{%0,%1,%2,%3,%4,%5,%6,%7,%8,%9,%10,%11,%12,%13,%14,%15,%16,%17,%18,%19}, {%20,%21,%22,%23}, db, p, 1, 1, 0;\n}\n"
    : "+f"(d[0]), "+f"(d[1]), "+f"(d[2]), "+f"(d[3]), "+f"(d[4]), "+f"(d[5]), "+f"(d[6]), "+f"(d[7]),
      "+f"(d[8]), "+f"(d[9]), "+f"(d[10]), "+f"(d[11]), "+f"(d[12]), "+f"(d[13]), "+f"(d[14]), "+f"(d[15]),
      "+f"(d[16]), "+f"(d[17]), "+f"(d[18]), "+f"(d[19])
    : "r"(a0), "r"(a1), "r"(a2), "r"(a3), "r"(blo), "n"(OFF), "n"(HI));
}
template <int OFF, int HI>
__device__ __forceinline__ void wgmma_rs_n32_init(float* d, uint32_t a0, uint32_t a1, uint32_t a2, uint32_t a3, uint32_t blo) {
  asm volatile("{\n.reg .pred p;\n.reg .b32 lo;\n.reg .b64 db;\n"
    "setp.ne.b32 p, 0, 0;\nadd.u32 lo, %20, %21;\nmov.b64 db, {lo, %22};\n"
    "wgmma.mma_async.sync.aligned.m64n32k16.f32.bf16.bf16 "
    "{%0,%1,%2,%3,%4,%5,%6,%7,%8,%9,%10,%11,%12,%13,%14,%15}, {%16,%17,%18,%19}, db, p, 1, 1, 0;\n}\n"
    : "=f"(d[0]), "=f"(d[1]), "=f"(d[2]), "=f"(d[3]), "=f"(d[4]), "=f"(d[5]), "=f"(d[6]), "=f"(d[7]),
      "=f"(d[8]), "=f"(d[9]), "=f"(d[10]), "=f"(d[11]), "=f"(d[12]), "=f"(d[13]), "=f"(d[14]), "=f"(d[15])
    : "r"(a0), "r"(a1), "r"(a2), "r"(a3), "r"(blo), "n"(OFF), "n"(HI));
}
template <int OFF, int HI>
__device__ __forceinline__ void wgmma_rs_n32_acc(float* d, uint32_t a0, uint32_t a1, uint32_t a2, uint32_t a3, uint32_t blo) {
  asm volatile("{\n.reg .pred p;\n.reg .b32 lo;\n.reg .b64 db;\n"
    "setp.ne.b32 p, 1, 0;\nadd.u32 lo, %20, %21;\nmov.b64 db, {lo, %22};\n"
    "wgmma.mma_async.sync.aligned.m64n32k16.f32.bf16.bf16 "
    "{%0,%1,%2,%3,%4,%5,%6,%7,%8,%9,%10,%11,%12,%13,%14,%15}, {%16,%17,%18,%19}, db, p, 1, 1, 0;\n}\n"
    : "+f"(d[0]), "+f"(d[1]), "+f"(d[2]), "+f"(d[3]), "+f"(d[4]), "+f"(d[5]), "+f"(d[6]), "+f"(d[7]),
      "+f"(d[8]), "+f"(d[9]), "+f"(d[10]), "+f"(d[11]), "+f"(d[12]), "+f"(d[13]), "+f"(d[14]), "+f"(d[15])
    : "r"(a0), "r"(a1), "r"(a2), "r"(a3), "r"(blo), "n"(OFF), "n"(HI));
}
template <int OFF, int HI>
__device__ __forceinline__ void wgmma_rs_n24_init(float* d, uint32_t a0, uint32_t a1, uint32_t a2, uint32_t a3, uint32_t blo) {
  asm volatile("{\n.reg .pred p;\n.reg .b32 lo;\n.reg .b64 db;\n"
    "setp.ne.b32 p, 0, 0;\nadd.u32 lo, %16, %17;\nmov.b64 db, {lo, %18};\n"
    "wgmma.mma_async.sync.aligned.m64n24k16.f32.bf16.bf16 "
    "{%0,%1,%2,%3,%4,%5,%6,%7,%8,%9,%10,%11}, {%12,%13,%14,%15}, db, p, 1, 1, 0;\n}\n"
    : "=f"(d[0]), "=f"(d[1]), "=f"(d[2]), "=f"(d[3]), "=f"(d[4]), "=f"(d[5]), "=f"(d[6]), "=f"(d[7]),
      "=f"(d[8]), "=f"(d[9]), "=f"(d[10]), "=f"(d[11])
    : "r"(a0), "r"(a1), "r"(a2), "r"(a3), "r"(blo), "n"(OFF), "n"(HI));
}
template <int OFF, int HI>
__device__ __forceinline__ void wgmma_rs_n24_acc(float* d, uint32_t a0, uint32_t a1, uint32_t a2, uint32_t a3, uint32_t blo) {
  asm volatile("{\n.reg .pred p;\n.reg .b32 lo;\n.reg .b64 db;\n"
    "setp.ne.b32 p, 1, 0;\nadd.u32 lo, %16, %17;\nmov.b64 db, {lo, %18};\n"
    "wgmma.mma_async.sync.aligned.m64n24k16.f32.bf16.bf16 "
    "{%0,%1,%2,%3,%4,%5,%6,%7,%8,%9,%10,%11}, {%12,%13,%14,%15}, db, p, 1, 1, 0;\n}\n"
    : "+f"(d[0]), "+f"(d[1]), "+f"(d[2]), "+f"(d[3]), "+f"(d[4]), "+f"(d[5]), "+f"(d[6]), "+f"(d[7]),
      "+f"(d[8]), "+f"(d[9]), "+f"(d[10]), "+f"(d[11])
    : "r"(a0), "r"(a1), "r"(a2), "r"(a3), "r"(blo), "n"(OFF), "n"(HI));
}
template <int OFF, int HI>
__device__ __forceinline__ void wgmma_rs_n16_init(float* d, uint32_t a0, uint32_t a1, uint32_t a2, uint32_t a3, uint32_t blo) {
  asm volatile("{\n.reg .pred p;\n.reg .b32 lo;\n.reg .b64 db;\n"
    "setp.ne.b32 p, 0, 0;\nadd.u32 lo, %12, %13;\nmov.b64 db, {lo, %14};\n"
    "wgmma.mma_async.sync.aligned.m64n16k16.f32.bf16.bf16 "
    "{%0,%1,%2,%3,%4,%5,%6,%7}, {%8,%9,%10,%11}, db, p, 1, 1, 0;\n}\n"
    : "=f"(d[0]), "=f"(d[1]), "=f"(d[2]), "=f"(d[3]), "=f"(d[4]), "=f"(d[5]), "=f"(d[6]), "=f"(d[7])
    : "r"(a0), "r"(a1), "r"(a2), "r"(a3), "r"(blo), "n"(OFF), "n"(HI));
}
template <int OFF, int HI>
__device__ __forceinline__ void wgmma_rs_n16_acc(float* d, uint32_t a0, uint32_t a1, uint32_t a2, uint32_t a3, uint32_t blo) {
  asm volatile("{\n.reg .pred p;\n.reg .b32 lo;\n.reg .b64 db;\n"
    "setp.ne.b32 p, 1, 0;\nadd.u32 lo, %12, %13;\nmov.b64 db, {lo, %14};\n"
    "wgmma.mma_async.sync.aligned.m64n16k16.f32.bf16.bf16 "
    "{%0,%1,%2,%3,%4,%5,%6,%7}, {%8,%9,%10,%11}, db, p, 1, 1, 0;\n}\n"
    : "+f"(d[0]), "+f"(d[1]), "+f"(d[2]), "+f"(d[3]), "+f"(d[4]), "+f"(d[5]), "+f"(d[6]), "+f"(d[7])
    : "r"(a0), "r"(a1), "r"(a2), "r"(a3), "r"(blo), "n"(OFF), "n"(HI));
}
template <int OFF, int HI>
__device__ __forceinline__ void wgmma_rs_n8_init(float* d, uint32_t a0, uint32_t a1, uint32_t a2, uint32_t a3, uint32_t blo) {
  asm volatile("{\n.reg .pred p;\n.reg .b32 lo;\n.reg .b64 db;\n"
    "setp.ne.b32 p, 0, 0;\nadd.u32 lo, %8, %9;\nmov.b64 db, {lo, %10};\n"
    "wgmma.mma_async.sync.aligned.m64n8k16.f32.bf16.bf16 "
    "{%0,%1,%2,%3}, {%4,%5,%6,%7}, db, p, 1, 1, 0;\n}\n"
    : "=f"(d[0]), "=f"(d[1]), "=f"(d[2]), "=f"(d[3])
    : "r"(a0), "r"(a1), "r"(a2), "r"(a3), "r"(blo), "n"(OFF), "n"(HI));
}
template <int OFF, int HI>
__device__ __forceinline__ void wgmma_rs_n8_acc(float* d, uint32_t a0, uint32_t a1, uint32_t a2, uint32_t a3, uint32_t blo) {
  asm volatile("{\n.reg .pred p;\n.reg .b32 lo;\n.reg .b64 db;\n"
    "setp.ne.b32 p, 1, 0;\nadd.u32 lo, %8, %9;\nmov.b64 db, {lo, %10};\n"
    "wgmma.mma_async.sync.aligned.m64n8k16.f32.bf16.bf16 "
    "{%0,%1,%2,%3}, {%4,%5,%6,%7}, db, p, 1, 1, 0;\n}\n"
    : "+f"(d[0]), "+f"(d[1]), "+f"(d[2]), "+f"(d[3])
    : "r"(a0), "r"(a1), "r"(a2), "r"(a3), "r"(blo), "n"(OFF), "n"(HI));
}

#define WG_FENCE()  asm volatile("wgmma.fence.sync.aligned;" ::: "memory")
#define WG_COMMIT() asm volatile("wgmma.commit_group.sync.aligned;" ::: "memory")
#define WG_WAIT(n)  asm volatile("wgmma.wait_group.sync.aligned %0;" :: "n"(n) : "memory")

__device__ __forceinline__ void mbar_init(uint32_t bar, uint32_t count) {
    asm volatile("mbarrier.init.shared::cta.b64 [%0], %1;" :: "r"(bar), "r"(count) : "memory");
}
__device__ __forceinline__ void mbar_wait(uint32_t bar, uint32_t parity) {
    asm volatile("{\n.reg .pred p;\n.reg .u32 n;\nmov.u32 n, 0;\n"
                 "MBAR_LOOP:\n"
                 "mbarrier.try_wait.parity.shared::cta.b64 p, [%0], %1;\n"
                 "@p bra MBAR_DONE;\n"
                 "add.u32 n, n, 1;\n"
                 "setp.lt.u32 p, n, 4194304;\n"
                 "@p bra MBAR_LOOP;\n"
                 "MBAR_DONE:\n}\n" :: "r"(bar), "r"(parity) : "memory");
}
__device__ __forceinline__ uint32_t mbar_test(uint32_t bar, uint32_t parity) {
    uint32_t ok;
    asm volatile("{\n.reg .pred p;\nmbarrier.test_wait.parity.shared::cta.b64 p, [%1], %2;\nselp.u32 %0, 1, 0, p;\n}\n"
                 : "=r"(ok) : "r"(bar), "r"(parity) : "memory");
    return ok;
}
__device__ __forceinline__ void mbar_wait_unless(uint32_t ok, uint32_t bar, uint32_t parity) {
    asm volatile("{\n.reg .pred p;\n.reg .u32 n;\n"
                 "setp.ne.u32 p, %2, 0;\n"
                 "@p bra MBAR_DONE;\n"
                 "mov.u32 n, 0;\n"
                 "MBAR_LOOP:\n"
                 "mbarrier.try_wait.parity.shared::cta.b64 p, [%0], %1;\n"
                 "@p bra MBAR_DONE;\n"
                 "add.u32 n, n, 1;\n"
                 "setp.lt.u32 p, n, 4194304;\n"
                 "@p bra MBAR_LOOP;\n"
                 "MBAR_DONE:\n}\n" :: "r"(bar), "r"(parity), "r"(ok) : "memory");
}
template <int N> __device__ __forceinline__ void sched_fence(float (&a)[N], float (&b)[N], float (&r)[4], float& c, uint32_t key, uint32_t pat, float one);
template <> __device__ __forceinline__ void sched_fence<8>(float (&a)[8], float (&b)[8], float (&r)[4], float& c, uint32_t key, uint32_t pat, float one) {
    asm volatile("{\n.reg .pred p;\n.reg .u32 n;\n"
                 "setp.ne.u32 p, %21, %23;\n"
                 "@p bra.uni SF_DONE;\n"
                 "mul.f32 %0, %0, %22;\nmul.f32 %1, %1, %22;\nmul.f32 %2, %2, %22;\nmul.f32 %3, %3, %22;\n"
                 "mul.f32 %4, %4, %22;\nmul.f32 %5, %5, %22;\nmul.f32 %6, %6, %22;\nmul.f32 %7, %7, %22;\n"
                 "mul.f32 %8, %8, %22;\nmul.f32 %9, %9, %22;\nmul.f32 %10, %10, %22;\nmul.f32 %11, %11, %22;\n"
                 "mul.f32 %12, %12, %22;\nmul.f32 %13, %13, %22;\nmul.f32 %14, %14, %22;\nmul.f32 %15, %15, %22;\n"
                 "mul.f32 %16, %16, %22;\nmul.f32 %17, %17, %22;\nmul.f32 %18, %18, %22;\nmul.f32 %19, %19, %22;\n"
                 "mul.f32 %20, %20, %22;\n"
                 "SF_DONE:\n}\n"
                 : "+f"(a[0]), "+f"(a[1]), "+f"(a[2]), "+f"(a[3]), "+f"(a[4]), "+f"(a[5]), "+f"(a[6]), "+f"(a[7]), "+f"(b[0]), "+f"(b[1]), "+f"(b[2]), "+f"(b[3]), "+f"(b[4]), "+f"(b[5]), "+f"(b[6]), "+f"(b[7]), "+f"(r[0]), "+f"(r[1]), "+f"(r[2]), "+f"(r[3]), "+f"(c)
                 : "r"(key), "f"(one), "r"(pat));
}
template <> __device__ __forceinline__ void sched_fence<16>(float (&a)[16], float (&b)[16], float (&r)[4], float& c, uint32_t key, uint32_t pat, float one) {
    asm volatile("{\n.reg .pred p;\n"
                 "setp.ne.u32 p, %37, %39;\n"
                 "@p bra.uni SF_DONE;\n"
                 "mul.f32 %0, %0, %38;\nmul.f32 %1, %1, %38;\nmul.f32 %2, %2, %38;\nmul.f32 %3, %3, %38;\n"
                 "mul.f32 %4, %4, %38;\nmul.f32 %5, %5, %38;\nmul.f32 %6, %6, %38;\nmul.f32 %7, %7, %38;\n"
                 "mul.f32 %8, %8, %38;\nmul.f32 %9, %9, %38;\nmul.f32 %10, %10, %38;\nmul.f32 %11, %11, %38;\n"
                 "mul.f32 %12, %12, %38;\nmul.f32 %13, %13, %38;\nmul.f32 %14, %14, %38;\nmul.f32 %15, %15, %38;\n"
                 "mul.f32 %16, %16, %38;\nmul.f32 %17, %17, %38;\nmul.f32 %18, %18, %38;\nmul.f32 %19, %19, %38;\n"
                 "mul.f32 %20, %20, %38;\nmul.f32 %21, %21, %38;\nmul.f32 %22, %22, %38;\nmul.f32 %23, %23, %38;\n"
                 "mul.f32 %24, %24, %38;\nmul.f32 %25, %25, %38;\nmul.f32 %26, %26, %38;\nmul.f32 %27, %27, %38;\n"
                 "mul.f32 %28, %28, %38;\nmul.f32 %29, %29, %38;\nmul.f32 %30, %30, %38;\nmul.f32 %31, %31, %38;\n"
                 "mul.f32 %32, %32, %38;\nmul.f32 %33, %33, %38;\nmul.f32 %34, %34, %38;\nmul.f32 %35, %35, %38;\n"
                 "mul.f32 %36, %36, %38;\n"
                 "SF_DONE:\n}\n"
                 : "+f"(a[0]), "+f"(a[1]), "+f"(a[2]), "+f"(a[3]), "+f"(a[4]), "+f"(a[5]), "+f"(a[6]), "+f"(a[7]), "+f"(a[8]), "+f"(a[9]), "+f"(a[10]), "+f"(a[11]), "+f"(a[12]), "+f"(a[13]), "+f"(a[14]), "+f"(a[15]), "+f"(b[0]), "+f"(b[1]), "+f"(b[2]), "+f"(b[3]), "+f"(b[4]), "+f"(b[5]), "+f"(b[6]), "+f"(b[7]), "+f"(b[8]), "+f"(b[9]), "+f"(b[10]), "+f"(b[11]), "+f"(b[12]), "+f"(b[13]), "+f"(b[14]), "+f"(b[15]), "+f"(r[0]), "+f"(r[1]), "+f"(r[2]), "+f"(r[3]), "+f"(c)
                 : "r"(key), "f"(one), "r"(pat));
}
__device__ __forceinline__ void mbar_arrive(uint32_t bar) {
    asm volatile("mbarrier.arrive.shared::cta.b64 _, [%0];" :: "r"(bar) : "memory");
}
__device__ __forceinline__ void mbar_arrive_cluster(uint32_t bar, uint32_t cta) {
    asm volatile("{\n.reg .b32 ra;\nmapa.shared::cluster.u32 ra, %0, %1;\n"
                 "mbarrier.arrive.shared::cluster.b64 _, [ra];\n}\n" :: "r"(bar), "r"(cta) : "memory");
}
__device__ __forceinline__ void mbar_expect_tx(uint32_t bar, uint32_t bytes) {
    asm volatile("mbarrier.arrive.expect_tx.shared::cta.b64 _, [%0], %1;" :: "r"(bar), "r"(bytes) : "memory");
}
__device__ __forceinline__ void cp_async16(uint32_t dst, const void* src) {
    asm volatile("cp.async.cg.shared.global [%0], [%1], 16;" :: "r"(dst), "l"(src) : "memory");
}
__device__ __forceinline__ const void* addr64(uint32_t lo, uint32_t hi, uint32_t off) {
    uint64_t p;
    asm volatile("{\n.reg .u32 l, h;\nadd.cc.u32 l, %1, %3;\naddc.u32 h, %2, 0;\nmov.b64 %0, {l, h};\n}"
                 : "=l"(p) : "r"(lo), "r"(hi), "r"(off));
    return (const void*)p;
}
__device__ __forceinline__ void cp_async_arrive(uint32_t bar) {
    asm volatile("cp.async.mbarrier.arrive.noinc.shared::cta.b64 [%0];" :: "r"(bar) : "memory");
}
__device__ __forceinline__ void l2_prefetch(const void* p, uint32_t bytes) {
    asm volatile("cp.async.bulk.prefetch.L2.global [%0], %1;" :: "l"(p), "r"(bytes) : "memory");
}
__device__ __forceinline__ float bf_lo(uint32_t v) { return __uint_as_float(v << 16); }
__device__ __forceinline__ float bf_hi(uint32_t v) { return __uint_as_float(v & 0xffff0000u); }
__device__ __forceinline__ float tanh_fast(float x) {
    float y;
    asm("tanh.approx.f32 %0, %1;" : "=f"(y) : "f"(x));
    return y;
}

constexpr int HI_SW128 = 0x40000040;
constexpr int HI_U     = 16;

#define SFENCE 0
template <int E>
__device__ __forceinline__ void tile_pos_e(int tile, int& kk, int& J) {
    constexpr int P = E / 7, K = E % 7, base = s_base(P, K);
    if constexpr (E > 0) tile_pos_e<E - 1>(tile, kk, J);
    if constexpr (s_nb(P, K) > 0) { if (tile >= base) { kk = K; J = s_j1(P) - 1 - (tile - base); } }
}
template <int Q>
__device__ __forceinline__ void tile_pos(int tile, int& kk, int& J) { tile_pos_e<13>(tile, kk, J); }
template <int P, int KK>
__device__ __forceinline__ void pnn_instr(float* d, const uint32_t (&a)[7][4], uint32_t ulo) {
#define DROPM 0
    constexpr int nb = ((DROPM >> (7 * P + KK)) & 1) ? 0 : s_nb(P, KK), off = s_base(P, KK) * 16;
    if constexpr (SFENCE && KK > 0 && nb > 0) { if constexpr (nb != s_nb(P, KK - 1)) WG_FENCE(); }
    #define PNN_CASE(NB, N) \
    if constexpr (nb == NB) { \
        if constexpr (KK == 0) wgmma_rs_n##N##_init<off, HI_U>(d, a[KK][0], a[KK][1], a[KK][2], a[KK][3], ulo); \
        else                   wgmma_rs_n##N##_acc <off, HI_U>(d, a[KK][0], a[KK][1], a[KK][2], a[KK][3], ulo); }
    PNN_CASE(1, 8) PNN_CASE(2, 16) PNN_CASE(3, 24) PNN_CASE(4, 32) PNN_CASE(5, 40) PNN_CASE(6, 48) PNN_CASE(7, 56) PNN_CASE(8, 64)
    PNN_CASE(9, 72) PNN_CASE(11, 88) PNN_CASE(13, 104)
    #undef PNN_CASE
}
template <int Q0, int Q1, int J0, int KK = 0>
__device__ __forceinline__ void pnn_phase(float* acc, const uint32_t (&a)[7][4], uint32_t ulo) {
    if constexpr (KK < 7) { pnn_instr<Q0 ? 1 : 0, KK>(acc, a, ulo); pnn_phase<Q0, Q1, J0, KK + 1>(acc, a, ulo); }
}
#define ACC_BLK(nb_, NB0_, NB1_) ((NB1_) - 1 - (nb_))
#define DOTCH 4
template <int NB0, int NB1>
__device__ __forceinline__ void pnn_dot(const float* pacc, const uint32_t (&a)[7][4], float& s0, float& s1, float& s2, float& s3) {
    #pragma unroll
    for (int nb = NB0; nb < NB1; nb++) {
        const uint32_t r0 = a[nb >> 1][(nb & 1) * 2], r1 = a[nb >> 1][(nb & 1) * 2 + 1];
        const float* p = pacc + ACC_BLK(nb, NB0, NB1) * 4;
        s0 = fmaf(p[0], __uint_as_float(r0 << 16), s0);
        s1 = fmaf(p[1], __uint_as_float(r0 & 0xffff0000u), s1);
        s2 = fmaf(p[2], __uint_as_float(r1 << 16), s2);
        s3 = fmaf(p[3], __uint_as_float(r1 & 0xffff0000u), s3);
    }
}
template <int NB0, int NB1>
__device__ __forceinline__ void pnn_dot_dep(const float* pacc, const uint32_t (&a)[7][4], float& s0, float& s1, float& s2, float& s3, uint32_t zero) {
    uint32_t sh, mk;
    asm volatile("lop3.b32 %0, %2, %3, 16, 0xEA;\nlop3.b32 %1, %2, %3, 0xffff0000, 0xEA;" : "=r"(sh), "=r"(mk) : "r"(__float_as_uint(pacc[0])), "r"(zero));
    #pragma unroll
    for (int nb = NB0; nb < NB1; nb++) {
        const uint32_t r0 = a[nb >> 1][(nb & 1) * 2], r1 = a[nb >> 1][(nb & 1) * 2 + 1];
        const float* p = pacc + ACC_BLK(nb, NB0, NB1) * 4;
        s0 = fmaf(p[0], __uint_as_float(r0 << sh), s0);
        s1 = fmaf(p[1], __uint_as_float(r0 & mk), s1);
        s2 = fmaf(p[2], __uint_as_float(r1 << sh), s2);
        s3 = fmaf(p[3], __uint_as_float(r1 & mk), s3);
    }
}
__device__ __forceinline__ void pnn_order(uint32_t (&a)[7][4], float s0, float s1, float s2, float s3, uint32_t zero) {
    asm volatile("lop3.b32 %0, %0, %4, %8, 0xf8;\nlop3.b32 %1, %1, %5, %8, 0xf8;\n"
                 "lop3.b32 %2, %2, %6, %8, 0xf8;\nlop3.b32 %3, %3, %7, %8, 0xf8;"
                 : "+r"(a[0][0]), "+r"(a[0][1]), "+r"(a[0][2]), "+r"(a[0][3])
                 : "r"(__float_as_uint(s0)), "r"(__float_as_uint(s1)), "r"(__float_as_uint(s2)), "r"(__float_as_uint(s3)), "r"(zero));
}
template <int K0, int K1>
__device__ __forceinline__ void pnn_ldsm(uint32_t (&a)[7][4], uint32_t xs, int t) {
    #pragma unroll
    for (int kk = K0; kk < K1; kk++) {
        if (kk < 6) {
            asm volatile("ldmatrix.sync.aligned.m8n8.x4.trans.shared.b16 {%0,%1,%2,%3}, [%4];"
                         : "=r"(a[kk][0]), "=r"(a[kk][1]), "=r"(a[kk][2]), "=r"(a[kk][3]) : "r"(xs + kk * 2048) : "memory");
        } else {
            asm volatile("ldmatrix.sync.aligned.m8n8.x2.trans.shared.b16 {%0,%1}, [%2];"
                         : "=r"(a[6][0]), "=r"(a[6][1]) : "r"(xs + 6 * 2048) : "memory");
            if (t >= 2) { a[6][0] = 0; a[6][1] = 0; }
            a[6][2] = 0; a[6][3] = 0;
        }
    }
}

template <int C>
__device__ __forceinline__ void tma_w1(uint32_t dst, const CUtensorMap* tm, uint32_t bar, int f, uint32_t rank) {
    int c1, c2;
    uint32_t off;
    if (C == 8)      { c2 = rank >> 1; c1 = f * 64 + (rank & 1) * 32; off = (rank >> 1) * 8192 + (rank & 1) * 4096; }
    else if (C == 4) { c2 = rank;      c1 = f * 64; off = rank * 8192; }
    else if (C == 2) { c2 = rank * 2;  c1 = f * 64; off = rank * 16384; }
    else             { c2 = 0;         c1 = f * 64; off = 0; }
    if (C == 1) {
        asm volatile("cp.async.bulk.tensor.3d.shared::cluster.global.mbarrier::complete_tx::bytes "
                     "[%0], [%1, {%3, %4, %5}], [%2];"
                     :: "r"(dst + off), "l"(tm), "r"(bar), "r"(0), "r"(c1), "r"(c2) : "memory");
    } else {
        asm volatile("cp.async.bulk.tensor.3d.shared::cluster.global.mbarrier::complete_tx::bytes.multicast::cluster "
                     "[%0], [%1, {%3, %4, %5}], [%2], %6;"
                     :: "r"(dst + off), "l"(tm), "r"(bar), "r"(0), "r"(c1), "r"(c2),
                        "h"((uint16_t)((1u << C) - 1)) : "memory");
    }
}

#define PT(n_, on_) do { } while (0)
#define TR(addr_, on_) do { } while (0)
#define CWAIT(bar, ph) mbar_wait(bar, ph)
#define OFF_TRX 0
#define GAP(x_) do { } while (0)
#define GAPV 0
#define SCHED 6
#define STAG 6
#define DEF_NOFF 2
#define TOUCH 0
#define PF_IDX_AT -1
#define PF_W1_AT -1
#define PF_W1_LEAD -1
#define PSTART -1
#define PF_TAB 0
#define PF_CHUNK 10240
#define REG_P 56
#define REG_C 224
#define HWAIT true
#define HPF 2
#define B2EARLY 1
#define CLUSTER 1
constexpr int NHELP = 4;
constexpr uint32_t BAR_FULL_H = 128, BAR_EMPTY_H = 128 + 16 * HS;
static_assert(BAR_U + 8 <= BAR_FULL_H && BAR_EMPTY_H + 16 * HS <= BAR_GO && 2 * P_BYTES >= NF * NF * 2 + 128, "barrier area");
__device__ unsigned long long g_xch[128 * 16];
#define DYN_KD 2
#define DYN_TAIL 1
#define DYN_RJ 104
static_assert(DYN_RJ % 4 == 0 && DYN_RJ <= 104 && DYN_KD % 2 == 0 && DEF_NOFF == 2 && DYN_KD <= 4 && 128 / NHELP * 2 * DEF_NOFF + 2 * DYN_KD <= 192 && 4 * DEF_NOFF + 4 <= 16, "hand-over of late tiles");
__device__ uint32_t g_rank;
__device__ uint32_t g_req[NHELP * DYN_KD * 2];
#define STR2(x) #x
#define STR(x) STR2(x)

__device__ __forceinline__ void build_u(uint32_t sw, uint32_t su, int tid) {
        #pragma unroll 2
        for (int c = tid; c < U_TILES * 16; c += 256) {
            const int tile = c >> 4, h = (c >> 3) & 1, r = c & 7;
            int kk, J;
            tile_pos<NG - 1>(tile, kk, J);
            const int j = 8 * J + r, i0 = 16 * kk + 8 * h;
            const int n16 = j < NF ? 16 * (j - i0 + 1) : 0;
            const uint32_t xa = sw + (i0 * NF + j) * 2, ya = sw + (j * NF + i0) * 2;
            uint16_t x[8];
            uint32_t y[4], pk[4];
            #pragma unroll
            for (int e = 0; e < 8; e++) asm volatile("ld.shared.u16 %0, [%1];" : "=h"(x[e]) : "r"(xa + e * NF * 2));
            asm volatile("ld.shared.v2.u32 {%0,%1}, [%2];" : "=r"(y[0]), "=r"(y[1]) : "r"(ya));
            asm volatile("ld.shared.v2.u32 {%0,%1}, [%2];" : "=r"(y[2]), "=r"(y[3]) : "r"(ya + 8));
            #pragma unroll
            for (int p = 0; p < 4; p++) {
                uint32_t mx, my;
                asm("shl.b32 %0, 0xffffffff, %1;" : "=r"(mx) : "r"(max(n16 - 32 * p, 0)));
                asm("shl.b32 %0, 0xffffffff, %1;" : "=r"(my) : "r"(max(n16 - 16 - 32 * p, 0)));
                const uint32_t xv = ((uint32_t)x[2 * p] | ((uint32_t)x[2 * p + 1] << 16)) & ~mx, yv = y[p] & ~my;
                asm("add.rn.bf16x2 %0, %1, %2;" : "=r"(pk[p]) : "r"(xv), "r"(yv));
            }
            asm volatile("st.shared.v4.u32 [%0], {%1,%2,%3,%4};"
                         :: "r"(su + tile * 256 + h * 128 + r * 16), "r"(pk[0]), "r"(pk[1]), "r"(pk[2]), "r"(pk[3]) : "memory");
        }
}

template <int C, int NOFF>
__global__ void __launch_bounds__(384, 1)
pnn_mlp_kernel(const __grid_constant__ CUtensorMap tmW1,
               const int* __restrict__ idx, const __nv_bfloat16* __restrict__ table,
               const __nv_bfloat16* __restrict__ wp, const __nv_bfloat16* __restrict__ w1,
               const __nv_bfloat16* __restrict__ b1,
               const __nv_bfloat16* __restrict__ w2, const __nv_bfloat16* __restrict__ b2,
               __nv_bfloat16* __restrict__ out, uint32_t table_bytes)
{
    extern __shared__ __align__(1024) uint8_t smem_raw[];
    PT(0, threadIdx.x == 0);
    const uint32_t sb = ((uint32_t)__cvta_generic_to_shared(smem_raw) + 1023u) & ~1023u;
    const uint32_t bars = sb + OFF_BAR;
    const int tid = threadIdx.x;
    const int warp = __shfl_sync(0xffffffffu, tid >> 5, 0), lane = tid & 31;
    constexpr int NHC = NOFF > 0 ? NHELP : 0;
    const bool helper = NOFF > 0 && blockIdx.x < NHC;
    const int cta = (int)blockIdx.x - NHC;
    const int row0 = cta * TILE_M;
    uint32_t rank = 0;
    if (C > 1) asm("mov.u32 %0, %%cluster_ctarank;" : "=r"(rank));

    int4 n0 = make_int4(0, 0, 0, 0), n1 = n0;
    uint32_t bb0 = 0, ww0 = 0;
    if (helper) {
    } else if (warp == 8 || warp == 9) {
        const int prow = (lane >> 3) + 4 * (lane & 1) + 8 * ((lane & 7) >> 1);
        n0 = __ldg((const int4*)(idx + (size_t)(row0 + 64 * (warp - 8) + prow) * NF));
        n1 = __ldg((const int4*)(idx + (size_t)(row0 + 64 * (warp - 8) + 32 + prow) * NF));
    } else if (warp < 4) {
        bb0 = __ldg((const uint32_t*)b1 + tid);
        ww0 = __ldg((const uint32_t*)w2 + tid);
    } else if (B2EARLY && tid == 128) {
        bb0 = __ldg((const unsigned short*)b2);
    }
    if (tid == 0) {
        #pragma unroll
        for (int s = 0; s < NS; s++) {
            mbar_init(bars + BAR_FULL_M + 8 * s, 64 + 1);
            mbar_init(bars + BAR_EMPTY_M + 8 * s, 8 * C);
        }
        #pragma unroll
        for (int s = 0; s < NP; s++) {
            mbar_init(bars + BAR_FULL_P + 8 * s, 64);
            mbar_init(bars + BAR_EMPTY_P + 8 * s, 4);
        }
        mbar_init(bars + BAR_WP, 1);
        mbar_init(bars + BAR_U, 1);
        mbar_init(bars + BAR_GO, 1);
        if (helper) {
            #pragma unroll
            for (int s = 0; s < 2 * HS; s++) {
                mbar_init(bars + BAR_FULL_H + 8 * s, 64);
                mbar_init(bars + BAR_EMPTY_H + 8 * s, 4);
            }
        }
        asm volatile("fence.mbarrier_init.release.cluster;" ::: "memory");
        mbar_expect_tx(bars + BAR_WP, NF * NF * 2);
        asm volatile("cp.async.bulk.shared::cluster.global.mbarrier::complete_tx::bytes [%0], [%1], %2, [%3];"
                     :: "r"(sb + (helper ? OFF_HW : OFF_P)), "l"(wp), "r"(NF * NF * 2), "r"(bars + BAR_WP) : "memory");
    }
    __syncthreads();
    if (C > 1) {
        asm volatile("barrier.cluster.arrive.release.aligned;" ::: "memory");
        asm volatile("barrier.cluster.wait.acquire.aligned;" ::: "memory");
    }

    PT(1, tid == 0);
    if (warp >= 8) {
        asm volatile("setmaxnreg.dec.sync.aligned.u32 " STR(REG_P) ";");
        const uint64_t tb = (uint64_t)table + (lane & 7) * 16;
        const uint32_t tlo = (uint32_t)tb, thi = (uint32_t)(tb >> 32);
        const int r4 = lane >> 3;
        const uint32_t c16 = (lane & 7) << 4;
        if (helper) {
            constexpr int G = 2 * NOFF > 0 ? 2 * NOFF : 1, HLAG = (HS + 2 + G - 1) / G;
            const int v = warp & 1, w = (warp - 8) >> 1;
            const int per = ((int)gridDim.x - NHC) / NHELP, c0 = blockIdx.x * per, ns = per * G;
            const int nt = ns + 2 * DYN_KD;
            const int* ip = idx + (size_t)(c0 * TILE_M + 64 * w + 64 - G) * NF + 52 * v + 4 * (lane & 7) + r4;
            const bool hi_ok = (lane & 7) < 5 - v;
            int ia[4], ib[4];
            int ql = 0;
            uint32_t lt = 0;
            #define H_LATE(mi_) (idx + (size_t)(((lt >> (4 * ((mi_) - ns))) & 255) * TILE_M + 64 * w + 64 - G - 2) * NF \
                                 + 52 * v + 4 * (lane & 7) + r4)
            #define H_NEXT(e_, mi_) do { \
                if ((e_) == 1) ip = (mi_) < ns ? ip + (TILE_M - G) * NF : H_LATE(mi_); \
                if ((e_) == 3 && (mi_) >= ns) ip = H_LATE(mi_); \
                if ((mi_) < nt) { ia[((e_) + 3) & 3] = __ldg(ip); ib[((e_) + 3) & 3] = hi_ok ? __ldg(ip + 32) : 0; } \
                ip += NF; } while (0)
            #define H_IDX(e_, on_) do { if (ql == G) { ql = 0; ip += (TILE_M - G) * NF; } \
                if (on_) { ia[e_] = __ldg(ip); ib[e_] = hi_ok ? __ldg(ip + 32) : 0; } ip += NF; ql++; } while (0)
            H_IDX(0, true); H_IDX(1, true); H_IDX(2, true);
            const int* gp = idx + (size_t)(c0 * TILE_M + 64 * w + 64 - G) * NF;
            if (HPF > 0 && v == 0 && lane >= 1 && lane < HPF && lane < per) l2_prefetch(gp + lane * TILE_M * NF, G * NF * 4);
            const uint32_t x0 = sb + w * HS * P_BYTES + (52 * v + r4) * 128 + (c16 ^ ((r4 + 4 * v) << 4));
            const uint32_t hp = sb + OFF_HPN + w * nt * 16;
            unsigned long long old = 0;
            float mine = 0.f;
            int q = 0, c = c0;
            #define HP(v_) do { } while (0)
            for (int m0 = 0; m0 < (HWAIT ? nt : 0); m0 += 4) {
                if (m0 == ns - 4) {
                    uint32_t val = lane < DYN_KD ? 0u : 1u;
                    const uint32_t* rq = &g_req[(blockIdx.x * DYN_KD + lane) * 2 + w];
                    for (uint32_t n = 0; n < (1u << 22) && val == 0; n++)
                        asm volatile("ld.relaxed.gpu.global.u32 %0, [%1];" : "=r"(val) : "l"(rq) : "memory");
                    lt = __reduce_or_sync(0xffffffffu, lane < DYN_KD && val ? (val - 1) << (8 * lane) : 0u);
                }
                #pragma unroll
                for (int e = 0; e < 4; e++) {
                const int m = m0 + e;
                const uint32_t sl = HS == 4 ? e : m & (HS - 1);
                const uint32_t c0_ = (uint32_t)ia[e] << 7, c1_ = (uint32_t)ib[e] << 7;
                if (G == 4) H_NEXT(e, m + 3); else
                H_IDX((e + 3) & 3, m + 3 < ns);
                const void* p[13];
                #pragma unroll
                for (int k = 0; k < 13; k++) p[k] = addr64(tlo, thi, __shfl_sync(0xffffffffu, k < 8 ? c0_ : c1_, k & 7, 8));
                #pragma unroll
                for (int k = 0; k < 13; k++) asm volatile("" : "+l"(p[k]));
                const uint32_t xE = x0 + sl * P_BYTES, xO = xE ^ 64;
                HP(tq0);
                if (m == HS - 2) mbar_wait(bars + BAR_U, 0);
                mbar_wait(bars + BAR_EMPTY_H + 8 * (w * HS + sl), ((m / HS) & 1) ^ 1);
                HP(tq1);
                #pragma unroll
                for (int k = 0; k < 13; k++)
                    if (k < 12 || v == 0) cp_async16(((k & 1) ? xO : xE) + k * 512, p[k]);
                cp_async_arrive(bars + BAR_FULL_H + 8 * (w * HS + sl));
                HP(tq2);
                if (DYN_KD > 0 && G == 4 ? e == 3 && m < ns : ++q == G) {
                    q = 0;
                    if (HPF > 0 && v == 0 && lane == 0 && c - c0 + HPF < per) l2_prefetch(gp + (c - c0 + HPF) * TILE_M * NF, G * NF * 4);
                    if (v == 1 && m >= (HLAG + 1) * G - 1 && lane < G) {
                        const int cp = c - HLAG;
                        if ((uint32_t)(old >> 32) == 2) {
                            out[(cp - 1) * TILE_M + 64 * w + 64 - G + lane] = __float2bfloat16_rn(__uint_as_float((uint32_t)old) + mine);
                            *(volatile unsigned long long*)&g_xch[(cp - 1) * 16 + 2 * lane + w] = 0;
                        }
                        float p0, p1, p2, p3;
                        asm volatile("ld.shared.v4.f32 {%0,%1,%2,%3}, [%4];" : "=f"(p0), "=f"(p1), "=f"(p2), "=f"(p3)
                                     : "r"(hp + (m + 1 - (HLAG + 1) * G + lane) * 16) : "memory");
                        mine = (p0 + p1) + (p2 + p3);
                        old = atomicExch(&g_xch[cp * 16 + 2 * lane + w], (1ull << 32) | __float_as_uint(mine));
                    }
                    __syncwarp();
                    c++;
                }
                HP(tq3);
                }
            }
            if (v == 1 && ns >= (HLAG + 1) * G && lane < G && (uint32_t)(old >> 32) == 2) {
                const int cp = c - HLAG - 1;
                out[cp * TILE_M + 64 * w + 64 - G + lane] = __float2bfloat16_rn(__uint_as_float((uint32_t)old) + mine);
                *(volatile unsigned long long*)&g_xch[cp * 16 + 2 * lane + w] = 0;
            }
        } else
        if (warp < 10) {
            const int u = warp - 8;
            const int prow = r4 + 4 * (lane & 1) + 8 * ((lane & 7) >> 1);
            const int4* ip = (const int4*)(idx + (size_t)(row0 + 64 * u + prow) * NF);
            const uint32_t lb = sb + u * 8192 + r4 * 128 + (c16 ^ (r4 << 4));
            if (warp == 8 && lane == 0) {
                #pragma unroll
                for (int s = 0; s < NS; s++) {
                    mbar_expect_tx(bars + BAR_FULL_M + 8 * s, 32768);
                    tma_w1<C>(sb + s * STAGE_BYTES + W_OFF, &tmW1, bars + BAR_FULL_M + 8 * s, s, rank);
                }
                const uint32_t share = (table_bytes / gridDim.x) & ~15u;
                const uint32_t npf = min(share, (uint32_t)PF_TAB);
                for (uint32_t o = 0; o < npf; o += PF_CHUNK)
                    l2_prefetch((const char*)table + blockIdx.x * share + o, min((uint32_t)PF_CHUNK, npf - o));
            }
            __syncwarp();
            int st = 0; uint32_t ph = 1;
            for (int g = 0; g < NF / 4; g++) {
                #pragma unroll
                for (int e = 0; e < 4; e++) {
                    const int f = g * 4 + e;
                    const uint32_t i0 = (uint32_t)(e == 0 ? n0.x : e == 1 ? n0.y : e == 2 ? n0.z : n0.w) << 7;
                    const uint32_t i1 = (uint32_t)(e == 0 ? n1.x : e == 1 ? n1.y : e == 2 ? n1.z : n1.w) << 7;
                    const void* p[16];
                    #pragma unroll
                    for (int i = 0; i < 16; i++) p[i] = addr64(tlo, thi, __shfl_sync(0xffffffffu, i < 8 ? i0 : i1, i & 7, 8));
                    #pragma unroll
                    for (int i = 0; i < 16; i++) asm volatile("" : "+l"(p[i]));
                    if (e == 3 && g + 1 < NF / 4) {
                        asm volatile("ld.global.nc.v4.u32 {%0,%1,%2,%3}, [%4];"
                                     : "=r"(n0.x), "=r"(n0.y), "=r"(n0.z), "=r"(n0.w) : "l"(ip + g + 1));
                        asm volatile("ld.global.nc.v4.u32 {%0,%1,%2,%3}, [%4];"
                                     : "=r"(n1.x), "=r"(n1.y), "=r"(n1.z), "=r"(n1.w) : "l"(ip + g + 1 + 32 * NF / 4));
                    }
                    const uint32_t fb = bars + BAR_FULL_M + 8 * st;
                    uint32_t dE = lb + st * STAGE_BYTES, dO = (dE ^ 64) + 512;
                    asm volatile("" : "+r"(dE), "+r"(dO));
                    if (f == 0) PT(9, tid == 256);
                    TR(sb + OFF_TRX + 8192 + f * 12, tid == 256);
                    mbar_wait(bars + BAR_EMPTY_M + 8 * st, ph);
                    TR(sb + OFF_TRX + 8192 + f * 12 + 4, tid == 256);
                    if (warp == 8 && lane == 0) {
                        if (f >= NS) {
                            mbar_expect_tx(fb, 32768);
                            tma_w1<C>(sb + st * STAGE_BYTES + W_OFF, &tmW1, fb, f, rank);
                        }
                    }
                    #pragma unroll
                    for (int i = 0; i < 16; i++) {
                        cp_async16(((i & 1) ? dO : dE) + ((i & 7) >> 1) * 1024 + (i >> 3) * 4096 + GAPV, p[i]);
                        GAP(gapv);
                    }
                    cp_async_arrive(fb);
                    if (PSTART >= 0 && f == PSTART && warp == 9 && lane == 0) mbar_arrive(bars + BAR_GO);
                    if (PF_W1_LEAD >= 0 && warp == 9 && f == max(0, cta * 25 / 32 - PF_W1_LEAD) && lane < 4 && cta < 128) {
                        const uint32_t wshare = NF * ND * NH * 2 / 128;
                        l2_prefetch((const char*)w1 + cta * wshare + lane * (wshare / 4), wshare / 4);
                    }
                    if (f == 0) PT(10, tid == 256);
                    if (f == 2) PT(11, tid == 256);
                    TR(sb + OFF_TRX + 8192 + f * 12 + 8, tid == 256);
                    if (++st == NS) { st = 0; ph ^= 1; }
                }
            }
        } else {
            const int v = warp - 10;
            const int* ip = idx + (size_t)row0 * NF + 52 * v + 4 * (lane & 7) + r4;
            const bool hi_ok = (lane & 7) < 5 - v;
            int a0 = __ldg(ip), a1 = hi_ok ? __ldg(ip + 32) : 0;
            int b0 = __ldg(ip + 64 * NF), b1_ = hi_ok ? __ldg(ip + 64 * NF + 32) : 0;
            const uint32_t xE = sb + OFF_P + (52 * v + r4) * 128 + (c16 ^ ((r4 + 4 * v) << 4)), xO = xE ^ 64;
            const uint32_t zero_p = (uint32_t)(out == nullptr);
            mbar_wait(bars + BAR_U, 0);
            if (PSTART >= 0) mbar_wait(bars + BAR_GO, 0);
            PT(12, tid == 320);
            int jend = TILE_M - 4 * NOFF;
            uint32_t arr = 0;
            const int* ipj = ip;
            int jrank = warp == 10 && lane == 0 ? DYN_RJ : -1;
            asm volatile("" : "+r"(jrank));
            for (int j0 = 0; j0 < jend; j0 += NP) {
                #pragma unroll
                for (int sl = 0; sl < NP; sl++) {
                    const int j = j0 + sl;
                    const uint32_t c0 = (uint32_t)a0 << 7, c1 = (uint32_t)a1 << 7;
                    a0 = b0; a1 = b1_;
                    if ((DYN_KD > 0 && NOFF > 0) || j + 2 < TILE_M - 4 * NOFF) {
                        const int* q = ipj + (64 * (sl & 1) + ((sl + 2) >> 1)) * NF;
                        b0 = __ldg(q);
                        b1_ = hi_ok ? __ldg(q + 32) : 0;
                    }
                    const void* p[13];
                    #pragma unroll
                    for (int m = 0; m < 13; m++) p[m] = addr64(tlo, thi, __shfl_sync(0xffffffffu, m < 8 ? c0 : c1, m & 7, 8));
                    #pragma unroll
                    for (int m = 0; m < 13; m++) asm volatile("" : "+l"(p[m]));
                    TR(sb + OFF_TRX + 8192 + 1280 + j * 12, tid == 320);
                    mbar_wait(bars + BAR_EMPTY_P + 8 * sl, ((j0 >> 2) & 1) ^ 1);
                    TR(sb + OFF_TRX + 8192 + 1280 + j * 12 + 4, tid == 320);
                    #pragma unroll
                    for (int m = 0; m < 13; m++)
                        { if (m < 12 || v == 0) cp_async16(((m & 1) ? xO : xE) + sl * P_BYTES + m * 512 + GAPV, p[m]); GAP(gapv); }
                    cp_async_arrive(bars + BAR_FULL_P + 8 * sl);
                    TR(sb + OFF_TRX + 8192 + 1280 + j * 12 + 8, tid == 320);
                }
                ipj += NP / 2 * NF;
                asm volatile("" : "+l"(ipj));
                if (NOFF > 0) {
                    asm volatile("{\n.reg .pred p;\nsetp.eq.s32 p, %2, %3;\n"
                                 "@p atom.relaxed.gpu.global.inc.u32 %0, [%1], %4;\n}"
                                 : "+r"(arr) : "l"(&g_rank), "r"(j0), "r"(jrank), "r"((int)gridDim.x - NHC - 1) : "memory");
                    if (j0 == DYN_RJ + NP) {
                        const int k = (int)arr - ((int)gridDim.x - NHC - NHELP * DYN_KD);
                        if (jrank >= 0 && k >= 0) {
                            volatile uint32_t* rq = &g_req[((k % NHELP) * DYN_KD + k / NHELP) * 2];
                            rq[0] = cta + 1; rq[1] = cta + 1;
                            asm volatile("st.shared.u32 [%0], %1;" :: "r"(bars + BAR_GO + 24), "r"(31) : "memory");
                        }
                        asm volatile("bar.sync 6, 64;" ::: "memory");
                        uint32_t np_;
                        asm volatile("ld.shared.u32 %0, [%1];" : "=r"(np_) : "r"(bars + BAR_GO + 24) : "memory");
                        jend = (np_ - NOFF) * 4;
                    }
                }
                if (j0 == PF_IDX_AT && warp == 11) {
                    if (lane < 8) l2_prefetch((const char*)(idx + (size_t)row0 * NF) + lane * (TILE_M * NF / 2), TILE_M * NF / 2);
                    __syncwarp();
                }
                if (j0 == PF_W1_AT && warp == 11) {
                    const uint32_t wshare = NF * ND * NH * 2 / 128;
                    if (lane < 4 && cta < 128)
                        l2_prefetch((const char*)w1 + cta * wshare + lane * (wshare / 4), wshare / 4);
                    __syncwarp();
                }
            }
        }
    } else {
        asm volatile("setmaxnreg.inc.sync.aligned.u32 " STR(REG_C) ";");
        const int w = warp >> 2;
        const int wq = warp & 3;
        const int g = lane >> 2, t = lane & 3;

        if (helper) {
            constexpr int G = 2 * NOFF > 0 ? 2 * NOFF : 2;
            mbar_wait(bars + BAR_WP, 0);
            build_u(sb + OFF_HW, sb + OFF_HU, tid);
            asm volatile("fence.proxy.async.shared::cta;" ::: "memory");
            asm volatile("bar.sync 1, 256;" ::: "memory");
            if (tid == 0) mbar_arrive(bars + BAR_U);
            const int per = ((int)gridDim.x - NHC) / NHELP, ns = per * G, nt = ns + 2 * DYN_KD;
            const uint32_t lrow = (lane & 7) + ((lane >> 4) & 1) * 8;
            const uint32_t xs = __shfl_sync(0xffffffffu,
                sb + w * HS * P_BYTES + lrow * 128 + (((wq * 2 + ((lane >> 3) & 1)) ^ (lane & 7)) << 4), lane);
            const uint32_t ulo = (((sb & 0x3FFFFu) + OFF_HU) >> 4) | (8u << 16);
            const uint32_t zero = (uint32_t)(out == nullptr);
            const uint32_t fb = bars + BAR_FULL_H + 8 * w * HS, eb = bars + BAR_EMPTY_H + 8 * w * HS;
            const uint32_t hp = sb + OFF_HPN + w * nt * 16;
            uint32_t a[7][4], b[7][4];
            float pa[52], pb[52];
            #define H_LOAD(r_, m_, on_) do { const uint32_t sl_ = (m_) & (HS - 1); \
                if (HWAIT && (on_)) mbar_wait(fb + 8 * sl_, ((m_) / HS) & 1); \
                pnn_ldsm<0, 7>(r_, xs + sl_ * P_BYTES, t); \
                __syncwarp(); if (lane == 0) mbar_arrive(eb + 8 * sl_); } while (0)
            #define H_MMA(p_, r_) do { WG_FENCE(); pnn_phase<0, NGA, 0>(p_, r_, ulo); pnn_phase<NGA, NG, 8>(p_ + NACC_A, r_, ulo); WG_COMMIT(); } while (0)
            #define H_DOT(v_, p_, r_) do { float s0 = 0.f, s1 = 0.f, s2 = 0.f, s3 = 0.f; \
                pnn_dot<0, NBA>(p_, r_, s0, s1, s2, s3); pnn_dot<NBA, 13>(p_ + NACC_A, r_, s0, s1, s2, s3); pnn_order(r_, s0, s1, s2, s3, zero); v_ = (s0 + s1) + (s2 + s3); } while (0)
            H_LOAD(a, 0, true);
            #pragma unroll 1
            for (int m = 0; m < nt; m += 2) {
                float v0, v1;
                H_MMA(pa, a);
                H_LOAD(b, m + 1, true);
                H_MMA(pb, b);
                WG_WAIT(1);
                H_DOT(v0, pa, a);
                H_LOAD(a, m + 2, m + 2 < nt);
                WG_WAIT(0);
                H_DOT(v1, pb, b);
                float u = (lane & 16) ? v1 : v0;
                u += __shfl_xor_sync(0xffffffffu, (lane & 16) ? v0 : v1, 16);
                u += __shfl_xor_sync(0xffffffffu, u, 8);
                u += __shfl_xor_sync(0xffffffffu, u, 4);
                u += __shfl_xor_sync(0xffffffffu, u, 2);
                u += __shfl_xor_sync(0xffffffffu, u, 1);
                if ((lane & 15) == 0)
                    asm volatile("st.shared.f32 [%0], %1;" :: "r"(hp + (m + (lane >> 4)) * 16 + wq * 4), "f"(u) : "memory");
            }
            asm volatile("bar.sync %0, 128;" :: "r"(2 + w) : "memory");
            constexpr int HLAG = (HS + 2 + G - 1) / G;
            const int q = tid & 127, mq = ns - HLAG * G + q;
            if (q < HLAG * G && mq >= 0) {
                const int c = blockIdx.x * per + mq / G, r = mq % G;
                float p0, p1, p2, p3;
                asm volatile("ld.shared.v4.f32 {%0,%1,%2,%3}, [%4];" : "=f"(p0), "=f"(p1), "=f"(p2), "=f"(p3)
                             : "r"(hp + mq * 16) : "memory");
                const float mine = (p0 + p1) + (p2 + p3);
                unsigned long long* slot = &g_xch[c * 16 + 2 * r + w];
                const unsigned long long old = atomicExch(slot, (1ull << 32) | __float_as_uint(mine));
                if ((uint32_t)(old >> 32) == 2) {
                    out[c * TILE_M + 64 * w + 64 - G + r] = __float2bfloat16_rn(__uint_as_float((uint32_t)old) + mine);
                    *(volatile unsigned long long*)slot = 0;
                }
            }
            if (q >= 64 && q < 96) {
                const int d = q - 64;
                uint32_t* rq = &g_req[(blockIdx.x * DYN_KD + (d >> 1)) * 2 + w];
                uint32_t val = 0;
                if (d < 2 * DYN_KD) asm volatile("ld.relaxed.gpu.global.u32 %0, [%1];" : "=r"(val) : "l"(rq) : "memory");
                __syncwarp();
                if (val != 0) {
                    if (!(d & 1)) *(volatile uint32_t*)rq = 0;
                    const int c = val - 1, r = d & 1;
                    float p0, p1, p2, p3;
                    asm volatile("ld.shared.v4.f32 {%0,%1,%2,%3}, [%4];" : "=f"(p0), "=f"(p1), "=f"(p2), "=f"(p3)
                                 : "r"(hp + (ns + d) * 16) : "memory");
                    const float mine = (p0 + p1) + (p2 + p3);
                    unsigned long long* slot = &g_xch[c * 16 + 2 * (G + r) + w];
                    const unsigned long long old = atomicExch(slot, (1ull << 32) | __float_as_uint(mine));
                    if ((uint32_t)(old >> 32) == 2) {
                        out[c * TILE_M + 64 * w + 64 - G - 2 + r] = __float2bfloat16_rn(__uint_as_float((uint32_t)old) + mine);
                        *(volatile unsigned long long*)slot = 0;
                    }
                }
            }
        } else {
        if (tid < 128)
            asm volatile("st.shared.v2.u32 [%0], {%1,%2};" :: "r"(sb + OFF_BW + tid * 8), "r"(bb0), "r"(ww0) : "memory");
        if (tid < 128)
            asm volatile("st.shared.v2.f32 [%0], {%1,%2};" :: "r"(sb + OFF_W2F + (tid >> 3) * 64 + (tid & 3) * 16 + ((tid >> 2) & 1) * 8),
                         "f"(0.5f * bf_lo(ww0)), "f"(0.5f * bf_hi(ww0)) : "memory");
        if (B2EARLY && tid == 128) asm volatile("st.shared.u32 [%0], %1;" :: "r"(bars + BAR_GO + 16), "r"(bb0 << 16) : "memory");
        if (tid == 129) asm volatile("st.shared.u32 [%0], %1;" :: "r"(bars + BAR_GO + 24), "r"(32) : "memory");
        asm volatile("bar.sync 1, 256;" ::: "memory");
        float acc[128];
        #pragma unroll
        for (int nb = 0; nb < 32; nb++) {
            uint32_t bb;
            asm volatile("ld.shared.u32 %0, [%1];" : "=r"(bb) : "r"(sb + OFF_BW + (nb * 4 + t) * 8));
            asm volatile("{\n.reg .b32 t;\nshl.b32 t, %4, 16;\nmov.b32 %0, t;\nmov.b32 %2, t;\n"
                         "and.b32 t, %4, 0xffff0000;\nmov.b32 %1, t;\nmov.b32 %3, t;\n}\n"
                         : "=f"(acc[nb * 4 + 0]), "=f"(acc[nb * 4 + 1]), "=f"(acc[nb * 4 + 2]), "=f"(acc[nb * 4 + 3]) : "r"(bb));
        }

        mbar_wait(bars + BAR_WP, 0);
        PT(2, tid == 0);
        build_u(sb + OFF_P, sb + OFF_U, tid);
        PT(3, tid == 0);
        asm volatile("fence.proxy.async.shared::cta;" ::: "memory");
        asm volatile("bar.sync 1, 256;" ::: "memory");
        if (tid == 0) mbar_arrive(bars + BAR_U);
        PT(4, tid == 0);

        const uint32_t lrow = (lane & 7) + ((lane >> 4) & 1) * 8;
        const uint32_t xs = __shfl_sync(0xffffffffu,
            sb + OFF_P + w * P_BYTES + lrow * 128 + (((wq * 2 + ((lane >> 3) & 1)) ^ (lane & 7)) << 4), lane);
        const uint32_t pn = sb + OFF_PN + (w * 4 + wq) * 4;
        const uint32_t sbl = sb & 0x3FFFFu;
        const uint32_t ulo = ((sbl + OFF_U) >> 4) | (8u << 16);
        const uint32_t alo = ((sbl + w * 8192) >> 4) | (1u << 16);
        const uint32_t blo = ((sbl + W_OFF) >> 4) | (512u << 16);
        const uint32_t zero = (uint32_t)(out == nullptr);

        #define RELEASE_STAGE(s_) do { if (lane < C) { \
            if (C == 1) mbar_arrive(bars + BAR_EMPTY_M + 8 * (s_)); \
            else mbar_arrive_cluster(bars + BAR_EMPTY_M + 8 * (s_), lane); } } while (0)
        #define RELEASE_SLOT(s_) do { __syncwarp(); if (lane == 0) mbar_arrive(bars + BAR_EMPTY_P + 8 * ((s_) * 2 + w)); } while (0)
        #define FULL_M(s_, ph_) do { \
            CWAIT(bars + BAR_FULL_M + 8 * (s_), ph_); \
            asm volatile("fence.proxy.async.shared::cta;" ::: "memory"); } while (0)
        #define FULL_P(s_, ph_) CWAIT(bars + BAR_FULL_P + 8 * ((s_) * 2 + w), ph_)
        #define MLP(s_, k_) wgmma_ss_n256<(s_) * (STAGE_BYTES >> 4) + 2 * (k_), (s_) * (STAGE_BYTES >> 4) + 128 * (k_), HI_SW128>(acc, alo, blo)

        PT(5, tid == 0);
        #define FT(f_) do { } while (0)
        FULL_M(0, 0); FT(0); PT(6, tid == 0); WG_FENCE(); MLP(0, 0); MLP(0, 1); MLP(0, 2); MLP(0, 3); WG_COMMIT();
        FULL_M(1, 0); FT(1); WG_FENCE(); MLP(1, 0); MLP(1, 1); MLP(1, 2); MLP(1, 3); WG_COMMIT();
        WG_WAIT(1); RELEASE_STAGE(0);
        FULL_M(2, 0); FT(2); WG_FENCE(); MLP(2, 0); MLP(2, 1); MLP(2, 2); MLP(2, 3); WG_COMMIT();
        WG_WAIT(1); RELEASE_STAGE(1);
        FULL_M(0, 1); FT(3); WG_FENCE(); MLP(0, 0); MLP(0, 1); MLP(0, 2); MLP(0, 3); WG_COMMIT();
        WG_WAIT(1); RELEASE_STAGE(2);
        #pragma unroll 1
        for (int i = 0; i < NOFF; i++) {
            const uint32_t ph = i & 1;
            FULL_M(1, ph ^ 1); FT(4 + 3 * i); WG_FENCE(); MLP(1, 0); MLP(1, 1); MLP(1, 2); MLP(1, 3); WG_COMMIT();
            WG_WAIT(1); RELEASE_STAGE(0);
            FULL_M(2, ph ^ 1); FT(5 + 3 * i); WG_FENCE(); MLP(2, 0); MLP(2, 1); MLP(2, 2); MLP(2, 3); WG_COMMIT();
            WG_WAIT(1); RELEASE_STAGE(1);
            FULL_M(0, ph); FT(6 + 3 * i); WG_FENCE(); MLP(0, 0); MLP(0, 1); MLP(0, 2); MLP(0, 3); WG_COMMIT();
            WG_WAIT(1); RELEASE_STAGE(2);
        }

        uint32_t a[7][4];
        PT(7, tid == 0);
        FULL_P(0, 0);
        PT(8, tid == 0);
        pnn_ldsm<0, KSA>(a, xs, t);
        FULL_M(1, (NOFF & 1) ^ 1);
        float v0 = 0.f, v1 = 0.f, u = 0.f, y;
        float s0 = 0.f, s1 = 0.f, s2 = 0.f, s3 = 0.f;

        #define SURE(ok_, bar_, ph_) mbar_wait_unless(ok_, bar_, ph_)
        #define TEST(bar_, ph_) mbar_test(bar_, ph_)
        #define TEST_M(s_, ph_) TEST(bars + BAR_FULL_M + 8 * (s_), ph_)
        #define TEST_P(s_, ph_) TEST(bars + BAR_FULL_P + 8 * ((s_) * 2 + w), ph_)
        #define SURE_M(ok_, s_, ph_) SURE(ok_, bars + BAR_FULL_M + 8 * (s_), ph_)
        #define SURE_P(ok_, s_, ph_) SURE(ok_, bars + BAR_FULL_P + 8 * ((s_) * 2 + w), ph_)
        #define RED_FIRST() do { y = __shfl_xor_sync(0xffffffffu, (lane & 16) ? v0 : v1, 16); u = (lane & 16) ? v1 : v0; } while (0)
        #define RED_STEP(o_) do { u += y; y = __shfl_xor_sync(0xffffffffu, u, o_); } while (0)
        #define RED_LAST(addr_, ok_) do { u += y; if ((lane & 15) == 0 && (ok_)) \
            asm volatile("st.shared.f32 [%0], %1;" :: "r"((addr_) + (lane >> 4) * 32), "f"(u) : "memory"); } while (0)

#define S7V 0
#define S8V 0
#define SBMASK 0x7e
        #define SBAR(n_) do { if ((SBMASK >> (n_)) & 1) asm volatile("{\n.reg .pred p;\nsetp.eq.u32 p, %0, 0;\n@p bra.uni SB_DONE;\n" \
            "nanosleep.u32 32;\nSB_DONE:\n}" :: "r"(zero) : "memory"); } while (0)
        #undef RED_FIRST
        #undef RED_STEP
        #define SHFLV(d_, v_, o_) asm volatile("shfl.sync.bfly.b32 %0, %1, %2, 0x1f, 0xffffffff;" : "=f"(d_) : "f"(v_), "n"(o_) : "memory")
        #define RED_FIRST() do { const float q_ = (lane & 16) ? v0 : v1; SHFLV(y, q_, 16); u = (lane & 16) ? v1 : v0; } while (0)
        #define RED_STEP(o_) do { u += y; SHFLV(y, u, o_); } while (0)
        int nper = 32;
        #pragma unroll 1
        for (int i = NOFF; i < nper; i++) {
            const uint32_t ph = i & 1, php = ph ^ (NOFF & 1);
            const bool more = i < 31;
            if (NOFF > 0)
                asm volatile("{\n.reg .pred p;\nsetp.eq.u32 p, %1, %3;\n@p ld.shared.u32 %0, [%2];\n}"
                             : "+r"(nper) : "r"(i), "r"(bars + BAR_GO + 24), "n"(DYN_RJ / 4 + NOFF + 2) : "memory");
            const bool moreP = i + 1 < nper;
            float pa[NACC_A > 0 ? NACC_A : 1], pb[NACC_B];
            uint32_t ok, okp;
            #define T(n) do { } while (0)
#define ALIGNM 0
            #define ALIGN(n_) do { if (((ALIGNM >> (n_)) & 1) && (more || STAG == 0)) asm volatile("bar.sync 5, 256;" ::: "memory"); } while (0)
            const uint32_t late = !more && w == 1, lead = !more && w == 0;
            #define STAG_AT(n_) do { if (STAG == (n_)) asm volatile("{\n.reg .pred p;\nsetp.ne.u32 p, %0, 0;\n@p bar.arrive 4, 256;\n}" :: "r"(lead) : "memory"); } while (0)
            if (late) {
                WG_WAIT(0);
                RELEASE_STAGE(0);
                asm volatile("bar.sync 4, 256;" ::: "memory");
            }
            ALIGN(0);
            WG_FENCE();
            pnn_phase<0, NGA, 0>(pa, a, ulo);
            WG_COMMIT();
            MLP(1, 0); MLP(1, 1);
            WG_COMMIT();
            SBAR(1);
            pnn_ldsm<KSA, 7>(a, xs, t);
            RELEASE_SLOT(0);
            WG_WAIT(1);
            if (!late) RELEASE_STAGE(0);
            RED_FIRST();
            s0 = s1 = s2 = s3 = 0.f;
            pnn_dot<0, NBA>(pa, a, s0, s1, s2, s3);
            ok = TEST_M(2, ph ^ 1);
            pnn_order(a, s0, s1, s2, s3, zero);
            RED_STEP(8);
            STAG_AT(1);
            SBAR(2);
            ALIGN(1);
            WG_FENCE();
            pnn_phase<NGA, NG, 8>(pb, a, ulo);
            WG_COMMIT();
            MLP(1, 2); MLP(1, 3);
            WG_COMMIT();
            STAG_AT(5);
            okp = TEST_P(1, php) | zero;
            SURE_M(ok, 2, ph ^ 1);
            WG_WAIT(1);
            STAG_AT(6);
            SURE_P(okp, 1, php);
            RED_STEP(4);
            pnn_ldsm<0, KSA>(a, xs + 2 * P_BYTES, t);
            WG_FENCE();
            MLP(2, 0); MLP(2, 1);
            WG_COMMIT();
            STAG_AT(2);
            SBAR(3);
            pnn_dot<NBA, 13>(pb, a, s0, s1, s2, s3);
            WG_WAIT(1);
            if (more) RELEASE_STAGE(1);
            pnn_order(a, s0, s1, s2, s3, zero);
            v0 = (s0 + s1) + (s2 + s3);
            STAG_AT(3);
            SBAR(4);
            ALIGN(2);
            WG_FENCE();
            pnn_phase<0, NGA, 0>(pa, a, ulo);
            WG_COMMIT();
            MLP(2, 2); MLP(2, 3);
            WG_COMMIT();
            SBAR(5);
            pnn_ldsm<KSA, 7>(a, xs + 2 * P_BYTES, t);
            RELEASE_SLOT(1);
            ok = TEST_M(0, ph);
            WG_WAIT(1);
            RED_STEP(2);
            s0 = s1 = s2 = s3 = 0.f;
            pnn_dot<0, NBA>(pa, a, s0, s1, s2, s3);
            RED_STEP(1);
            SURE_M(ok, 0, ph);
            okp = TEST_P(0, php ^ 1) | (uint32_t)!moreP;
            pnn_order(a, s0, s1, s2, s3, zero);
            STAG_AT(4);
            ALIGN(3);
            WG_FENCE();
            pnn_phase<NGA, NG, 8>(pb, a, ulo);
            WG_COMMIT();
            MLP(0, 0); MLP(0, 1);
            WG_COMMIT();
            WG_WAIT(2);
            if (more) RELEASE_STAGE(2);
            WG_WAIT(1);
            SURE_P(okp, 0, php ^ 1);
            RED_LAST(pn + (i - NOFF) * 64 - 64, i > NOFF);
            pnn_ldsm<0, KSA>(a, xs, t);
            WG_FENCE();
            MLP(0, 2); MLP(0, 3);
            WG_COMMIT();
            SBAR(6);
            ok = TEST_M(1, ph) | (uint32_t)!more;
            pnn_dot<NBA, 13>(pb, a, s0, s1, s2, s3);
            SURE_M(ok, 1, ph);
            pnn_order(a, s0, s1, s2, s3, zero);
            v1 = (s0 + s1) + (s2 + s3);
        }
        if (nper < 32) {
            if (w == 1) {
                WG_WAIT(0); RELEASE_STAGE(0);
                asm volatile("bar.sync 4, 256;" ::: "memory");
            }
            WG_FENCE(); MLP(1, 0); MLP(1, 1); MLP(1, 2); MLP(1, 3); WG_COMMIT();
            if (w == 0) { WG_WAIT(1); RELEASE_STAGE(0); }
            FULL_M(2, 0); WG_FENCE(); MLP(2, 0); MLP(2, 1); MLP(2, 2); MLP(2, 3); WG_COMMIT();
            if (w == 0) asm volatile("bar.arrive 4, 256;" ::: "memory");
        }
        RED_FIRST(); RED_STEP(8); RED_STEP(4); RED_STEP(2); RED_STEP(1); RED_LAST(pn + (nper - 1 - NOFF) * 64, true);
        asm volatile("bar.sync %0, 128;" :: "r"(2 + w) : "memory");
        float pre;
        {
            float p0, p1, p2, p3, b2v;
            asm volatile("ld.shared.v4.f32 {%0,%1,%2,%3}, [%4];"
                         : "=f"(p0), "=f"(p1), "=f"(p2), "=f"(p3)
                         : "r"(sb + OFF_PN + (2 * ((wq * 16 + g + (t & 1) * 8) & 63) + w) * 16) : "memory");
            asm volatile("ld.shared.f32 %0, [%1];" : "=f"(b2v) : "r"(bars + BAR_GO + 16) : "memory");
            const int mr = wq * 16 + g + (t & 1) * 8;
            pre = NOFF > 0 && mr >= 2 * nper - 2 * NOFF ? b2v : ((p0 + p1) + (p2 + p3)) + b2v;
        }
        if (nper < 32) {
            if (w == 1) asm volatile("bar.sync 7, 256;" ::: "memory");
            FULL_M(0, 1); WG_FENCE(); MLP(0, 0); MLP(0, 1); WG_COMMIT(); MLP(0, 2); MLP(0, 3); WG_COMMIT();
            if (w == 0) {
                if (DYN_TAIL == 1) WG_WAIT(1); else WG_WAIT(0);
                asm volatile("bar.arrive 7, 256;" ::: "memory");
            }
        }
        WG_WAIT(0);
        PT(13, tid == 0);
        const int mrow = w * 64 + wq * 16 + g + (t & 1) * 8;
        const bool offl = NOFF > 0 && t < 2 && (mrow & 63) >= 2 * nper - 2 * NOFF;
        const int xr = (mrow & 63) - (64 - 2 * NOFF);
        unsigned long long* const slot = &g_xch[offl ? cta * 16 + 2 * (xr >= 0 ? xr : xr + 2 * NOFF + 2) + w : 0];
        unsigned long long peek = 0;
        if (offl) asm volatile("ld.relaxed.gpu.global.u64 %0, [%1];" : "=l"(peek) : "l"(slot) : "memory");

        float r0 = 0.f, r1 = 0.f;
        {
            float ra[4] = {0.f, 0.f, 0.f, 0.f};
            #pragma unroll
            for (int n2 = 0; n2 < 16; n2++) {
                float wv[4];
                asm volatile("ld.shared.v4.f32 {%0,%1,%2,%3}, [%4];"
                             : "=f"(wv[0]), "=f"(wv[1]), "=f"(wv[2]), "=f"(wv[3]) : "r"(sb + OFF_W2F + n2 * 64 + t * 16));
                #pragma unroll
                for (int e = 0; e < 8; e++) {
                    const float x = acc[n2 * 8 + e];
                    const float u = x * fmaf(x * x, 0.7978845608028654f * 0.044715f, 0.7978845608028654f);
                    const float gl = fmaf(x, tanh_fast(u), x);
                    ra[e & 3] = fmaf(gl, wv[(e >> 2) * 2 + (e & 1)], ra[e & 3]);
                }
            }
            r0 = ra[0] + ra[1];
            r1 = ra[2] + ra[3];
        }
        r0 += __shfl_xor_sync(0xffffffffu, r0, 1);
        r0 += __shfl_xor_sync(0xffffffffu, r0, 2);
        r1 += __shfl_xor_sync(0xffffffffu, r1, 1);
        r1 += __shfl_xor_sync(0xffffffffu, r1, 2);
        PT(15, tid == 0);
        if (t < 2) {
            const int m = w * 64 + wq * 16 + g + t * 8;
            const float res = (t ? r1 : r0) + pre;
            if (!offl) {
                out[row0 + m] = __float2bfloat16_rn(res);
            } else {
                if ((uint32_t)(peek >> 32) != 1) peek = atomicExch(slot, (2ull << 32) | __float_as_uint(res));
                if ((uint32_t)(peek >> 32) == 1) {
                    out[row0 + m] = __float2bfloat16_rn(res + __uint_as_float((uint32_t)peek));
                    *(volatile unsigned long long*)slot = 0;
                }
            }
        }
        PT(14, tid == 0);
        }
    }
    if (C > 1) {
        __syncwarp();
        asm volatile("barrier.cluster.arrive.release.aligned;" ::: "memory");
        asm volatile("barrier.cluster.wait.acquire.aligned;" ::: "memory");
    }
}

typedef CUresult (*EncodeFn)(CUtensorMap*, CUtensorMapDataType, cuuint32_t, void*, const cuuint64_t*,
                             const cuuint64_t*, const cuuint32_t*, const cuuint32_t*, CUtensorMapInterleave,
                             CUtensorMapSwizzle, CUtensorMapL2promotion, CUtensorMapFloatOOBfill);

template <int C>
bool make_map(EncodeFn enc, CUtensorMap* tm, void* w1) {
    cuuint64_t dims[3]    = {64, (cuuint64_t)NF * ND, 4};
    cuuint64_t strides[2] = {NH * 2, 128};
    cuuint32_t box[3]     = {64, C == 8 ? 32u : 64u, C == 1 ? 4u : C == 2 ? 2u : 1u};
    cuuint32_t estr[3]    = {1, 1, 1};
    return enc(tm, CU_TENSOR_MAP_DATA_TYPE_BFLOAT16, 3, w1, dims, strides, box, estr,
               CU_TENSOR_MAP_INTERLEAVE_NONE, CU_TENSOR_MAP_SWIZZLE_128B,
               CU_TENSOR_MAP_L2_PROMOTION_L2_256B, CU_TENSOR_MAP_FLOAT_OOB_FILL_NONE) == CUDA_SUCCESS;
}

template <int C>
void fill_cfg(cudaLaunchConfig_t* cfg, cudaLaunchAttribute* at, int grid) {
    cfg->gridDim = dim3(grid); cfg->blockDim = dim3(384); cfg->dynamicSmemBytes = SMEM_BYTES;
    cfg->stream = cudaStreamPerThread;
    at[0].id = cudaLaunchAttributeClusterDimension;
    at[0].val.clusterDim.x = C; at[0].val.clusterDim.y = 1; at[0].val.clusterDim.z = 1;
    cfg->attrs = at; cfg->numAttrs = C > 1 ? 1 : 0;
}

template <int C, int NOFF>
void launch(EncodeFn enc, void* const* d_in, const int* in_sizes, void* d_out, int grid) {
    CUtensorMap tm;
    make_map<C>(enc, &tm, d_in[3]);
    cudaLaunchConfig_t cfg = {}; cudaLaunchAttribute at[1];
    fill_cfg<C>(&cfg, at, grid + (NOFF > 0 ? NHELP : 0));
    cudaLaunchKernelEx(&cfg, pnn_mlp_kernel<C, NOFF>, tm, (const int*)d_in[0], (const __nv_bfloat16*)d_in[1],
                       (const __nv_bfloat16*)d_in[2], (const __nv_bfloat16*)d_in[3], (const __nv_bfloat16*)d_in[4],
                       (const __nv_bfloat16*)d_in[5], (const __nv_bfloat16*)d_in[6], (__nv_bfloat16*)d_out,
                       (uint32_t)in_sizes[1] * 2u);
}

}

extern "C" void kernel_launch(void* const* d_in, const int* in_sizes, int n_in, void* d_out, int out_size) {
    (void)n_in; (void)out_size;
    static EncodeFn enc = nullptr;
    static bool helpers = false;
    const int grid = in_sizes[0] / (NF * TILE_M);
    if (!enc) {
        void* fn = nullptr; cudaDriverEntryPointQueryResult qr;
        cudaGetDriverEntryPoint("cuTensorMapEncodeTiled", &fn, cudaEnableDefault, &qr);
        enc = (EncodeFn)fn;
        cudaFuncSetAttribute(pnn_mlp_kernel<1, 0>, cudaFuncAttributeMaxDynamicSharedMemorySize, SMEM_BYTES);
        cudaFuncSetAttribute(pnn_mlp_kernel<CLUSTER, DEF_NOFF>, cudaFuncAttributeMaxDynamicSharedMemorySize, SMEM_BYTES);
        int dev = 0, sms = 0;
        cudaGetDevice(&dev);
        cudaDeviceGetAttribute(&sms, cudaDevAttrMultiProcessorCount, dev);
        helpers = DEF_NOFF > 0 && grid <= 128 && grid % NHELP == 0 && grid >= NHELP * DYN_KD && grid + NHELP <= sms;
    }
    if (helpers) launch<CLUSTER, DEF_NOFF>(enc, d_in, in_sizes, d_out, grid);
    else         launch<1, 0>(enc, d_in, in_sizes, d_out, grid);
}
```
